```python
import torch

def _softmax(x, axis=-1):
    return torch.softmax(x, dim=axis)

def _gelu(x):
    return torch.nn.functional.gelu(x, approximate='tanh')

def _silu(x):
    return torch.nn.functional.silu(x)

def _sigmoid(x):
    return torch.sigmoid(x)

def _layernorm(x, axis=-1, eps=1e-05):
    m = x.mean(dim=axis, keepdim=True)
    v = x.var(dim=axis, keepdim=True, unbiased=False)
    return (x - m) / torch.sqrt(v + eps)

def _scatter_add(tgt, idx, src, axis=0):
    return tgt.clone().index_add_(axis, idx, src)

def _segment_sum(src, seg, n):
    out = torch.zeros((n,) + src.shape[1:], dtype=src.dtype)
    return out.index_add_(0, seg, src)

def _pad(x, pw):
    flat = tuple((v for pair in reversed(pw) for v in pair))
    return torch.nn.functional.pad(x, flat)
kernel_name = 'concat_heads__sliding_local_dilated__memory_aug_recurrent_mem_tr__prompt'

def setup_inputs():

    _w = lambda a: (lambda t: t.to(torch.bfloat16) if t.is_floating_point() else t)(torch.as_tensor(a))

    def _A_setup():
        B, S, D = (1, 2048, 448)
        return {'x': _w((lambda *s: torch.randn(*s, dtype=torch.bfloat16) * 0.2)(B, S, D)), 'wqkv': _w((lambda *s: torch.randn(*s, dtype=torch.bfloat16) * 0.2)(D, 3 * D)), 'wo': _w((lambda *s: torch.randn(*s, dtype=torch.bfloat16) * 0.05)(D, D))}
    _A_in = _A_setup()

    def _B_setup():
        B, S, Dm = (1, 2048, 448)
        H, Dh = (16, 256)
        M, seg = (8, 32)
        seg = min(seg, S)
        S = S // seg * seg
        return {'x': _w((lambda *s: torch.randn(*s, dtype=torch.bfloat16) * 0.05)(B, S, Dm)), 'mem0': _w((lambda *s: torch.randn(*s, dtype=torch.bfloat16) * 1.6)(B, M, Dm)), 'Wq': _w((lambda *s: torch.randn(*s, dtype=torch.bfloat16) * 0.8)(Dm, H, Dh) * Dm ** (-0.5)), 'Wk': _w((lambda *s: torch.randn(*s, dtype=torch.bfloat16) * 0.8)(Dm, H, Dh) * Dm ** (-0.5)), 'Wv': _w((lambda *s: torch.randn(*s, dtype=torch.bfloat16) * 1.6)(Dm, H, Dh) * Dm ** (-0.5)), 'Wo': _w((lambda *s: torch.randn(*s, dtype=torch.bfloat16) * 1.6)(H, Dh, Dm) * (H * Dh) ** (-0.5)), 'seg_len': seg}
    _B_in = _B_setup()
    return {'A_x': _A_in['x'], 'A_wqkv': _A_in['wqkv'], 'A_wo': _A_in['wo'], 'B_x': _B_in['x'], 'B_mem0': _B_in['mem0'], 'B_Wq': _B_in['Wq'], 'B_Wk': _B_in['Wk'], 'B_Wv': _B_in['Wv'], 'B_Wo': _B_in['Wo'], 'B_seg_len': _B_in['seg_len']}

def reference(A_x, A_wqkv, A_wo, B_x, B_mem0, B_Wq, B_Wk, B_Wv, B_Wo, B_seg_len):

    def _A_ref(x, wqkv, wo):
        B, S, D = x.shape
        H = 16
        Dh = D // H
        W, dil = (8, 2)
        qkv = (lambda x, *d: x.permute(*d))((x @ wqkv).reshape(B, S, 3, H, Dh), 2, 0, 3, 1, 4)
        q, k, v = (qkv[0], qkv[1], qkv[2])
        scale = Dh ** (-0.5)
        pos = torch.arange(S)
        off = torch.arange(W) * dil
        idx = pos[:, None] - off[None, :]
        mask = idx >= 0
        idx_c = torch.where(mask, idx, 0).reshape(-1)
        kg = k[:, :, idx_c, :].reshape(B, H, S, W, Dh)
        vg = v[:, :, idx_c, :].reshape(B, H, S, W, Dh)
        logits = torch.einsum('bhsd,bhswd->bhsw', q, kg) * scale
        logits = torch.where(mask[None, None, :, :], logits, -1000000000.0)
        attn = _softmax(logits, axis=-1)
        o = torch.einsum('bhsw,bhswd->bhsd', attn, vg)
        return (lambda x, *d: x.permute(*d))(o, 0, 2, 1, 3).reshape(B, S, D) @ wo

    def _B_ref(x, mem0, Wq, Wk, Wv, Wo, seg_len):
        B, S, Dm = x.shape
        H, Dh = (Wq.shape[1], Wq.shape[2])
        M = mem0.shape[1]
        scale = Dh ** (-0.5)
        n_seg = S // seg_len
        L = M + seg_len
        idx = torch.arange(L)
        mask = (idx[:, None] < M) | (idx[:, None] >= idx[None, :])
        mem = mem0
        outs = []
        for s in range(n_seg):
            xs = x[:, s * seg_len:(s + 1) * seg_len, :].clone()
            h = torch.concatenate([mem, xs], axis=1)
            q = torch.einsum('btd,dhe->bhte', h, Wq)
            k = torch.einsum('btd,dhe->bhte', h, Wk)
            v = torch.einsum('btd,dhe->bhte', h, Wv)
            scores = torch.einsum('bhqe,bhke->bhqk', q, k) * scale
            scores = torch.where(mask[None, None], scores, -1000000000.0)
            p = _softmax(scores, axis=-1)
            o = torch.einsum('bhqk,bhke->bhqe', p, v)
            o = torch.einsum('bhte,hed->btd', o, Wo)
            mem = o[:, :M, :].clone()
            outs.append(o[:, M:, :])
        return torch.concatenate(outs, axis=1)
    a = _A_ref(A_x, A_wqkv, A_wo)
    b = _B_ref(B_x, B_mem0, B_Wq, B_Wk, B_Wv, B_Wo, B_seg_len)
    return torch.concatenate([a, b], axis=-1)
```

```cpp
#include <cuda_runtime.h>
#include <cuda_bf16.h>
#include <cuda.h>
#include <stdint.h>
#include <type_traits>

typedef __nv_bfloat16 bf16;
constexpr int NSEG = 64;
#define REP_ 2
constexpr int REP = REP_;
#define LAY 0
constexpr int RSTR = LAY == 0 ? 128 : LAY == 1 ? 512 : 256;
#define SSTR_(r) (LAY == 0 ? (r)*REP*128 : LAY == 1 ? (r)*128 : ((r) & 1)*128 + ((r) >> 1)*512)
constexpr int SPIN_MAX = 400000;

__device__ uint4 g_WF[2*16*28*28*32];
__device__ uint4 g_GF[64*16*28*2*32];
__device__ uint4 g_UF[64*16*28*2*32];
__device__ __align__(8192) uint4 g_MACC[69*4*REP*128];
__device__ uint2 g_WD[64*16*28*32];
__device__ uint4 g_SX[64*16*4*4*32];
__device__ __align__(1024) bf16 g_OA[2048*448];
constexpr int F_GU = 0, F_REC = F_GU + 56, F_A1 = F_REC + 64, F_Q1 = F_A1 + 18, F_Q2 = F_Q1 + 1, F_COUNT = F_Q2 + 1;
__device__ unsigned g_flag[F_COUNT*32];

__device__ __forceinline__ uint32_t smem_u32(const void* p){ return (uint32_t)__cvta_generic_to_shared(p);}
__device__ __forceinline__ uint32_t mapa(uint32_t a, uint32_t r){ uint32_t o; asm("mapa.shared::cluster.u32 %0, %1, %2;" : "=r"(o) : "r"(a), "r"(r)); return o;}
__device__ __forceinline__ void mbar_init(uint32_t a, uint32_t c){ asm volatile("mbarrier.init.shared::cta.b64 [%0], %1;" :: "r"(a), "r"(c) : "memory");}
__device__ __forceinline__ void mbar_expect_tx(uint32_t a, uint32_t b){ asm volatile("mbarrier.arrive.expect_tx.shared::cta.b64 _, [%0], %1;" :: "r"(a), "r"(b) : "memory");}
__device__ __forceinline__ void mbar_arrive(uint32_t a){ asm volatile("mbarrier.arrive.shared::cta.b64 _, [%0];" :: "r"(a) : "memory");}
__device__ __forceinline__ void mbar_arrive_remote(uint32_t a){ asm volatile("mbarrier.arrive.shared::cluster.b64 _, [%0];" :: "r"(a) : "memory");}
__device__ __forceinline__ void mbar_wait(uint32_t a, uint32_t ph){
  asm volatile("{\n.reg .pred p, q;\n.reg .u32 n;\nmov.u32 n, 0;\n"
    "LW%=:\nadd.u32 n, n, 1;\nsetp.lt.u32 q, n, 2000;\nmbarrier.try_wait.parity.shared::cta.b64 p, [%0], %1;\nand.pred q, q, !p;\n@q bra LW%=;\n}" :: "r"(a), "r"(ph) : "memory");
}
__device__ __forceinline__ void cluster_sync(){ asm volatile("barrier.cluster.arrive.relaxed.aligned; barrier.cluster.wait.aligned;" ::: "memory");}
__device__ __forceinline__ void bar_sync(int id, int n){ asm volatile("bar.sync %0, %1;" :: "r"(id), "r"(n) : "memory");}
__device__ __forceinline__ void bar_arrive(int id, int n){ asm volatile("bar.arrive %0, %1;" :: "r"(id), "r"(n) : "memory");}
__device__ __forceinline__ void fence_async(){ asm volatile("fence.proxy.async.global;" ::: "memory");}
__device__ __forceinline__ void fence_async_smem(){ asm volatile("fence.proxy.async.shared::cta;" ::: "memory");}
__device__ __forceinline__ bool elect(){ uint32_t p; asm volatile("{.reg .pred p; elect.sync _|p, 0xffffffff; selp.u32 %0,1,0,p;}" : "=r"(p)); return p;}
__device__ __forceinline__ uint4 lds128(uint32_t a){ uint4 v; asm volatile("ld.shared.v4.b32 {%0,%1,%2,%3}, [%4];" : "=r"(v.x), "=r"(v.y), "=r"(v.z), "=r"(v.w) : "r"(a) : "memory"); return v;}
__device__ __forceinline__ uint4 lds128v(uint32_t a){ uint4 v; asm volatile("ld.volatile.shared.v4.b32 {%0,%1,%2,%3}, [%4];" : "=r"(v.x), "=r"(v.y), "=r"(v.z), "=r"(v.w) : "r"(a) : "memory"); return v;}
__device__ __forceinline__ uint2 lds64(uint32_t a){ uint2 v; asm volatile("ld.shared.v2.b32 {%0,%1}, [%2];" : "=r"(v.x), "=r"(v.y) : "r"(a) : "memory"); return v;}
__device__ __forceinline__ uint2 lds64v(uint32_t a){ uint2 v; asm volatile("ld.volatile.shared.v2.b32 {%0,%1}, [%2];" : "=r"(v.x), "=r"(v.y) : "r"(a) : "memory"); return v;}
__device__ __forceinline__ uint32_t lds32(uint32_t a){ uint32_t v; asm volatile("ld.shared.b32 %0, [%1];" : "=r"(v) : "r"(a) : "memory"); return v;}
__device__ __forceinline__ void sts128(uint32_t a, uint4 v){ asm volatile("st.shared.v4.b32 [%0], {%1,%2,%3,%4};" :: "r"(a), "r"(v.x), "r"(v.y), "r"(v.z), "r"(v.w) : "memory");}
__device__ __forceinline__ void sts64(uint32_t a, uint32_t x, uint32_t y){ asm volatile("st.shared.v2.b32 [%0], {%1,%2};" :: "r"(a), "r"(x), "r"(y) : "memory");}
__device__ __forceinline__ void sts32(uint32_t a, uint32_t x){ asm volatile("st.shared.b32 [%0], %1;" :: "r"(a), "r"(x) : "memory");}
__device__ __forceinline__ void sts16(uint32_t a, uint32_t x){ asm volatile("{.reg .b16 lo, hi; mov.b32 {lo, hi}, %1; st.shared.b16 [%0], lo;}" :: "r"(a), "r"(x) : "memory");}
__device__ __forceinline__ void st_async1(uint32_t a, uint32_t x, uint32_t bar){ asm volatile("st.async.weak.shared::cluster.mbarrier::complete_tx::bytes.b32 [%0], %1, [%2];" :: "r"(a), "r"(x), "r"(bar) : "memory");}
__device__ __forceinline__ void st_async2(uint32_t a, uint32_t x, uint32_t y, uint32_t bar){ asm volatile("st.async.weak.shared::cluster.mbarrier::complete_tx::bytes.v2.b32 [%0], {%1,%2}, [%3];" :: "r"(a), "r"(x), "r"(y), "r"(bar) : "memory");}
__device__ __forceinline__ uint4 ld_relaxed4(const void* p){ uint4 v; asm volatile("ld.relaxed.gpu.global.v4.b32 {%0,%1,%2,%3}, [%4];" : "=r"(v.x), "=r"(v.y), "=r"(v.z), "=r"(v.w) : "l"(p) : "memory"); return v;}
__device__ __forceinline__ uint4 ldcg4(const void* p){ uint4 v; asm volatile("ld.global.cg.v4.b32 {%0,%1,%2,%3}, [%4];" : "=r"(v.x), "=r"(v.y), "=r"(v.z), "=r"(v.w) : "l"(p) : "memory"); return v;}
__device__ __forceinline__ uint2 ldcg2(const void* p){ uint2 v; asm volatile("ld.global.cg.v2.b32 {%0,%1}, [%2];" : "=r"(v.x), "=r"(v.y) : "l"(p) : "memory"); return v;}
__device__ __forceinline__ void red_bf16x8(void* p, uint32_t a, uint32_t b, uint32_t c, uint32_t d){ asm volatile("red.relaxed.gpu.global.add.noftz.v4.bf16x2 [%0], {%1,%2,%3,%4};" :: "l"(p), "r"(a), "r"(b), "r"(c), "r"(d) : "memory");}
__device__ __forceinline__ void flag_add(int f){ asm volatile("red.release.gpu.global.add.u32 [%0], 1;" :: "l"(g_flag + f*32) : "memory");}
__device__ __forceinline__ void flag_set(int f, unsigned v){ asm volatile("st.release.gpu.global.u32 [%0], %1;" :: "l"(g_flag + f*32), "r"(v) : "memory");}
__device__ __forceinline__ unsigned flag_get(int f){ unsigned v; asm volatile("ld.acquire.gpu.global.u32 %0, [%1];" : "=r"(v) : "l"(g_flag + f*32) : "memory"); return v;}
__device__ __forceinline__ void flag_wait(int f, unsigned n){ int i = 0; while (flag_get(f) < n && ++i < SPIN_MAX) __nanosleep(100); }
__device__ __forceinline__ void bulk_g2s(uint32_t dst, const void* src, uint32_t bytes, uint32_t bar){ asm volatile("cp.async.bulk.shared::cluster.global.mbarrier::complete_tx::bytes [%0], [%1], %2, [%3];" :: "r"(dst), "l"(src), "r"(bytes), "r"(bar) : "memory");}
__device__ __forceinline__ void bulk_g2s_last(uint32_t dst, const void* src, uint32_t bytes, uint32_t bar){
  asm volatile("{.reg .b64 pol; createpolicy.fractional.L2::evict_first.b64 pol, 1.0;\n"
    "cp.async.bulk.shared::cluster.global.mbarrier::complete_tx::bytes.L2::cache_hint [%0], [%1], %2, [%3], pol;}" :: "r"(dst), "l"(src), "r"(bytes), "r"(bar) : "memory");}
__device__ __forceinline__ void bulk_s2s(uint32_t dst, uint32_t src, uint32_t bytes, uint32_t bar){ asm volatile("cp.async.bulk.shared::cluster.shared::cta.mbarrier::complete_tx::bytes [%0], [%1], %2, [%3];" :: "r"(dst), "r"(src), "r"(bytes), "r"(bar) : "memory");}
__device__ __forceinline__ void tma2d(uint32_t dst, const CUtensorMap* m, int c0, int c1, uint32_t bar){ asm volatile("cp.async.bulk.tensor.2d.shared::cluster.global.mbarrier::complete_tx::bytes [%0], [%1, {%3, %4}], [%2];" :: "r"(dst), "l"(m), "r"(bar), "r"(c0), "r"(c1) : "memory");}
__device__ __forceinline__ void tma2d_mc(uint32_t dst, const CUtensorMap* m, int c0, int c1, uint32_t bar){ asm volatile("cp.async.bulk.tensor.2d.shared::cluster.global.mbarrier::complete_tx::bytes.multicast::cluster [%0], [%1, {%3, %4}], [%2], %5;" :: "r"(dst), "l"(m), "r"(bar), "r"(c0), "r"(c1), "h"((uint16_t)0xf) : "memory");}
__device__ __forceinline__ void tma2d_pf(const CUtensorMap* m, int c0, int c1){ asm volatile("cp.async.bulk.prefetch.tensor.2d.L2.global [%0, {%1, %2}];" :: "l"(m), "r"(c0), "r"(c1) : "memory");}
__device__ __forceinline__ uint32_t pack2(float lo, float hi){ uint32_t r; asm("cvt.rn.bf16x2.f32 %0, %1, %2;" : "=r"(r) : "f"(hi), "f"(lo)); return r;}
__device__ __forceinline__ uint32_t hadd2(uint32_t a, uint32_t b){ uint32_t d; asm("add.rn.bf16x2 %0, %1, %2;" : "=r"(d) : "r"(a), "r"(b)); return d;}
__device__ __forceinline__ uint4 hadd8(const uint4& a, const uint4& b) { return make_uint4(hadd2(a.x, b.x), hadd2(a.y, b.y), hadd2(a.z, b.z), hadd2(a.w, b.w)); }
__device__ __forceinline__ float bflo(uint32_t a){ return __uint_as_float(a << 16);}
__device__ __forceinline__ float bfhi(uint32_t a){ return __uint_as_float(a & 0xffff0000u);}
__device__ __forceinline__ uint32_t movm(uint32_t a){ uint32_t d; asm volatile("movmatrix.sync.aligned.m8n8.trans.b16 %0, %1;" : "=r"(d) : "r"(a)); return d;}
__device__ __forceinline__ float ex2(float x){ float y; asm("ex2.approx.ftz.f32 %0, %1;" : "=f"(y) : "f"(x)); return y;}
__device__ __forceinline__ float rcp(float x){ float y; asm("rcp.approx.ftz.f32 %0, %1;" : "=f"(y) : "f"(x)); return y;}
__device__ __forceinline__ float quad_max(float v){ const float a = __shfl_xor_sync(0xffffffffu, v, 1), b = __shfl_xor_sync(0xffffffffu, v, 2), c = __shfl_xor_sync(0xffffffffu, v, 3); return fmaxf(fmaxf(v, a), fmaxf(b, c)); }
__device__ __forceinline__ float quad_sum(float v){ v += __shfl_xor_sync(0xffffffffu, v, 1); return v + __shfl_xor_sync(0xffffffffu, v, 2); }
__device__ __forceinline__ void mma16(float (&d)[4], uint32_t a0, uint32_t a1, uint32_t a2, uint32_t a3, uint32_t b0, uint32_t b1) {
  asm volatile("mma.sync.aligned.m16n8k16.row.col.f32.bf16.bf16.f32 {%0,%1,%2,%3}, {%4,%5,%6,%7}, {%8,%9}, {%0,%1,%2,%3};"
    : "+f"(d[0]), "+f"(d[1]), "+f"(d[2]), "+f"(d[3]) : "r"(a0), "r"(a1), "r"(a2), "r"(a3), "r"(b0), "r"(b1));
}
__device__ __forceinline__ void mma16z(float (&d)[4], uint32_t a0, uint32_t a1, uint32_t a2, uint32_t a3, uint32_t b0, uint32_t b1) {
  asm volatile("mma.sync.aligned.m16n8k16.row.col.f32.bf16.bf16.f32 {%0,%1,%2,%3}, {%4,%5,%6,%7}, {%8,%9}, {%10,%10,%10,%10};"
    : "=f"(d[0]), "=f"(d[1]), "=f"(d[2]), "=f"(d[3]) : "r"(a0), "r"(a1), "r"(a2), "r"(a3), "r"(b0), "r"(b1), "f"(0.f));
}
__device__ __forceinline__ void mma8(float (&d)[4], uint32_t a0, uint32_t a1, uint32_t b0) {
  asm volatile("mma.sync.aligned.m16n8k8.row.col.f32.bf16.bf16.f32 {%0,%1,%2,%3}, {%4,%5}, {%6}, {%0,%1,%2,%3};"
    : "+f"(d[0]), "+f"(d[1]), "+f"(d[2]), "+f"(d[3]) : "r"(a0), "r"(a1), "r"(b0));
}
__device__ __forceinline__ void ldsm4(uint32_t (&r)[4], uint32_t a){ asm volatile("ldmatrix.sync.aligned.m8n8.x4.shared.b16 {%0,%1,%2,%3}, [%4];" : "=r"(r[0]), "=r"(r[1]), "=r"(r[2]), "=r"(r[3]) : "r"(a) : "memory");}
__device__ __forceinline__ void ldsm4t(uint32_t (&r)[4], uint32_t a){ asm volatile("ldmatrix.sync.aligned.m8n8.x4.trans.shared.b16 {%0,%1,%2,%3}, [%4];" : "=r"(r[0]), "=r"(r[1]), "=r"(r[2]), "=r"(r[3]) : "r"(a) : "memory");}
__device__ __forceinline__ void stsm4(uint32_t a, uint32_t r0, uint32_t r1, uint32_t r2, uint32_t r3){ asm volatile("stmatrix.sync.aligned.m8n8.x4.shared.b16 [%0], {%1,%2,%3,%4};" :: "r"(a), "r"(r0), "r"(r1), "r"(r2), "r"(r3) : "memory");}
__device__ __forceinline__ void stsm2(uint32_t a, uint32_t r0, uint32_t r1){ asm volatile("stmatrix.sync.aligned.m8n8.x2.shared.b16 [%0], {%1,%2};" :: "r"(a), "r"(r0), "r"(r1) : "memory");}
__device__ __forceinline__ uint32_t clk(){ unsigned long long c; asm volatile("mov.u64 %0, %%clock64;" : "=l"(c)); return (uint32_t)c;}
__device__ __forceinline__ uint32_t opaque(uint32_t v, int lane){ return __shfl_sync(0xffffffffu, v, lane); }
__device__ __forceinline__ void wg_fence(){ asm volatile("wgmma.fence.sync.aligned;" ::: "memory");}
__device__ __forceinline__ void wg_commit(){ asm volatile("wgmma.commit_group.sync.aligned;" ::: "memory");}
template<int N> __device__ __forceinline__ void wg_wait(){ asm volatile("wgmma.wait_group.sync.aligned %0;" :: "n"(N) : "memory");}
template<int N> __device__ __forceinline__ void wg_pin(float (&d)[N]){
  #pragma unroll
  for (int i = 0; i < N; i++) asm volatile("" : "+f"(d[i]) :: "memory");
}
__device__ __forceinline__ uint32_t wg_lo(uint32_t addr, uint32_t lbo){ return ((addr & 0x3ffff) >> 4) | ((lbo >> 4) << 16);}
constexpr uint32_t DH_SW = (1024 >> 4) | (1u << 30), DH_NS = 128 >> 4;
template<int I, int N, typename F> __device__ __forceinline__ void static_for(F&& f) { if constexpr (I < N) { f(std::integral_constant<int, I>()); static_for<I + 1, N>(f); } }
template<int TB, uint32_t BH, int BO, int ACC> __device__ __forceinline__ void wg_rs64(float (&d)[32], const uint4& a, uint32_t bl) {
  asm volatile("{.reg .pred p; .reg .b32 l; .reg .b64 db; setp.ne.b32 p, %40, 0; add.u32 l, %36, %37; mov.b64 db, {l, %38};\n"
    "wgmma.mma_async.sync.aligned.m64n64k16.f32.bf16.bf16 {%0,%1,%2,%3,%4,%5,%6,%7,%8,%9,%10,%11,%12,%13,%14,%15,%16,%17,%18,%19,%20,%21,%22,%23,%24,%25,%26,%27,%28,%29,%30,%31}, {%32,%33,%34,%35}, db, p, 1, 1, %39;}"
    : "+f"(d[0]), "+f"(d[1]), "+f"(d[2]), "+f"(d[3]), "+f"(d[4]), "+f"(d[5]), "+f"(d[6]), "+f"(d[7]), "+f"(d[8]), "+f"(d[9]), "+f"(d[10]), "+f"(d[11]), "+f"(d[12]), "+f"(d[13]), "+f"(d[14]), "+f"(d[15]), "+f"(d[16]), "+f"(d[17]), "+f"(d[18]), "+f"(d[19]), "+f"(d[20]), "+f"(d[21]), "+f"(d[22]), "+f"(d[23]), "+f"(d[24]), "+f"(d[25]), "+f"(d[26]), "+f"(d[27]), "+f"(d[28]), "+f"(d[29]), "+f"(d[30]), "+f"(d[31])
    : "r"(a.x), "r"(a.y), "r"(a.z), "r"(a.w), "r"(bl), "n"(BO >> 4), "n"(BH), "n"(TB), "n"(ACC));
}
template<int TA, uint32_t AH, int AO, int TB, uint32_t BH, int BO> __device__ __forceinline__ void wg_ss64(float (&d)[32], uint32_t al, uint32_t bl, int acc) {
  asm volatile("{.reg .pred p; .reg .b32 l, m; .reg .b64 da, db; setp.ne.b32 p, %40, 0; add.u32 l, %32, %33; mov.b64 da, {l, %34}; add.u32 m, %35, %36; mov.b64 db, {m, %37};\n"
    "wgmma.mma_async.sync.aligned.m64n64k16.f32.bf16.bf16 {%0,%1,%2,%3,%4,%5,%6,%7,%8,%9,%10,%11,%12,%13,%14,%15,%16,%17,%18,%19,%20,%21,%22,%23,%24,%25,%26,%27,%28,%29,%30,%31}, da, db, p, 1, 1, %38, %39;}"
    : "+f"(d[0]), "+f"(d[1]), "+f"(d[2]), "+f"(d[3]), "+f"(d[4]), "+f"(d[5]), "+f"(d[6]), "+f"(d[7]), "+f"(d[8]), "+f"(d[9]), "+f"(d[10]), "+f"(d[11]), "+f"(d[12]), "+f"(d[13]), "+f"(d[14]), "+f"(d[15]), "+f"(d[16]), "+f"(d[17]), "+f"(d[18]), "+f"(d[19]), "+f"(d[20]), "+f"(d[21]), "+f"(d[22]), "+f"(d[23]), "+f"(d[24]), "+f"(d[25]), "+f"(d[26]), "+f"(d[27]), "+f"(d[28]), "+f"(d[29]), "+f"(d[30]), "+f"(d[31])
    : "r"(al), "n"(AO >> 4), "n"(AH), "r"(bl), "n"(BO >> 4), "n"(BH), "n"(TA), "n"(TB), "r"(acc));
}
template<int TA, uint32_t AH, int AO, int TB, uint32_t BH, int BO> __device__ __forceinline__ void wg_ss112(float (&d)[56], uint32_t al, uint32_t bl, int acc) {
  asm volatile("{.reg .pred p; .reg .b32 l, m; .reg .b64 da, db; setp.ne.b32 p, %64, 0; add.u32 l, %56, %57; mov.b64 da, {l, %58}; add.u32 m, %59, %60; mov.b64 db, {m, %61};\n"
    "wgmma.mma_async.sync.aligned.m64n112k16.f32.bf16.bf16 {%0,%1,%2,%3,%4,%5,%6,%7,%8,%9,%10,%11,%12,%13,%14,%15,%16,%17,%18,%19,%20,%21,%22,%23,%24,%25,%26,%27,%28,%29,%30,%31,%32,%33,%34,%35,%36,%37,%38,%39,%40,%41,%42,%43,%44,%45,%46,%47,%48,%49,%50,%51,%52,%53,%54,%55}, da, db, p, 1, 1, %62, %63;}"
    : "+f"(d[0]), "+f"(d[1]), "+f"(d[2]), "+f"(d[3]), "+f"(d[4]), "+f"(d[5]), "+f"(d[6]), "+f"(d[7]), "+f"(d[8]), "+f"(d[9]), "+f"(d[10]), "+f"(d[11]), "+f"(d[12]), "+f"(d[13]), "+f"(d[14]), "+f"(d[15]), "+f"(d[16]), "+f"(d[17]), "+f"(d[18]), "+f"(d[19]), "+f"(d[20]), "+f"(d[21]), "+f"(d[22]), "+f"(d[23]), "+f"(d[24]), "+f"(d[25]), "+f"(d[26]), "+f"(d[27]), "+f"(d[28]), "+f"(d[29]), "+f"(d[30]), "+f"(d[31]), "+f"(d[32]), "+f"(d[33]), "+f"(d[34]), "+f"(d[35]), "+f"(d[36]), "+f"(d[37]), "+f"(d[38]), "+f"(d[39]), "+f"(d[40]), "+f"(d[41]), "+f"(d[42]), "+f"(d[43]), "+f"(d[44]), "+f"(d[45]), "+f"(d[46]), "+f"(d[47]), "+f"(d[48]), "+f"(d[49]), "+f"(d[50]), "+f"(d[51]), "+f"(d[52]), "+f"(d[53]), "+f"(d[54]), "+f"(d[55])
    : "r"(al), "n"(AO >> 4), "n"(AH), "r"(bl), "n"(BO >> 4), "n"(BH), "n"(TA), "n"(TB), "r"(acc));
}
template<int TA, uint32_t AH, int AO, int TB, uint32_t BH, int BO> __device__ __forceinline__ void wg_ss224(float (&d)[112], uint32_t al, uint32_t bl, int acc) {
  asm volatile("{.reg .pred p; .reg .b32 l, m; .reg .b64 da, db; setp.ne.b32 p, %120, 0; add.u32 l, %112, %113; mov.b64 da, {l, %114}; add.u32 m, %115, %116; mov.b64 db, {m, %117};\n"
    "wgmma.mma_async.sync.aligned.m64n224k16.f32.bf16.bf16 {%0,%1,%2,%3,%4,%5,%6,%7,%8,%9,%10,%11,%12,%13,%14,%15,%16,%17,%18,%19,%20,%21,%22,%23,%24,%25,%26,%27,%28,%29,%30,%31,%32,%33,%34,%35,%36,%37,%38,%39,%40,%41,%42,%43,%44,%45,%46,%47,%48,%49,%50,%51,%52,%53,%54,%55,%56,%57,%58,%59,%60,%61,%62,%63,%64,%65,%66,%67,%68,%69,%70,%71,%72,%73,%74,%75,%76,%77,%78,%79,%80,%81,%82,%83,%84,%85,%86,%87,%88,%89,%90,%91,%92,%93,%94,%95,%96,%97,%98,%99,%100,%101,%102,%103,%104,%105,%106,%107,%108,%109,%110,%111}, da, db, p, 1, 1, %118, %119;}"
    : "+f"(d[0]), "+f"(d[1]), "+f"(d[2]), "+f"(d[3]), "+f"(d[4]), "+f"(d[5]), "+f"(d[6]), "+f"(d[7]), "+f"(d[8]), "+f"(d[9]), "+f"(d[10]), "+f"(d[11]), "+f"(d[12]), "+f"(d[13]), "+f"(d[14]), "+f"(d[15]), "+f"(d[16]), "+f"(d[17]), "+f"(d[18]), "+f"(d[19]), "+f"(d[20]), "+f"(d[21]), "+f"(d[22]), "+f"(d[23]), "+f"(d[24]), "+f"(d[25]), "+f"(d[26]), "+f"(d[27]), "+f"(d[28]), "+f"(d[29]), "+f"(d[30]), "+f"(d[31]), "+f"(d[32]), "+f"(d[33]), "+f"(d[34]), "+f"(d[35]), "+f"(d[36]), "+f"(d[37]), "+f"(d[38]), "+f"(d[39]), "+f"(d[40]), "+f"(d[41]), "+f"(d[42]), "+f"(d[43]), "+f"(d[44]), "+f"(d[45]), "+f"(d[46]), "+f"(d[47]), "+f"(d[48]), "+f"(d[49]), "+f"(d[50]), "+f"(d[51]), "+f"(d[52]), "+f"(d[53]), "+f"(d[54]), "+f"(d[55]), "+f"(d[56]), "+f"(d[57]), "+f"(d[58]), "+f"(d[59]), "+f"(d[60]), "+f"(d[61]), "+f"(d[62]), "+f"(d[63]), "+f"(d[64]), "+f"(d[65]), "+f"(d[66]), "+f"(d[67]), "+f"(d[68]), "+f"(d[69]), "+f"(d[70]), "+f"(d[71]), "+f"(d[72]), "+f"(d[73]), "+f"(d[74]), "+f"(d[75]), "+f"(d[76]), "+f"(d[77]), "+f"(d[78]), "+f"(d[79]), "+f"(d[80]), "+f"(d[81]), "+f"(d[82]), "+f"(d[83]), "+f"(d[84]), "+f"(d[85]), "+f"(d[86]), "+f"(d[87]), "+f"(d[88]), "+f"(d[89]), "+f"(d[90]), "+f"(d[91]), "+f"(d[92]), "+f"(d[93]), "+f"(d[94]), "+f"(d[95]), "+f"(d[96]), "+f"(d[97]), "+f"(d[98]), "+f"(d[99]), "+f"(d[100]), "+f"(d[101]), "+f"(d[102]), "+f"(d[103]), "+f"(d[104]), "+f"(d[105]), "+f"(d[106]), "+f"(d[107]), "+f"(d[108]), "+f"(d[109]), "+f"(d[110]), "+f"(d[111])
    : "r"(al), "n"(AO >> 4), "n"(AH), "r"(bl), "n"(BO >> 4), "n"(BH), "n"(TA), "n"(TB), "r"(acc));
}

__host__ __device__ __forceinline__ int slot_dim(int rho, int t) {
  const int u = rho >> 2, c = rho & 3;
  if (t == 6) return 8*(12 + (u >> 1)) + 2*c + (u & 1);
  return 8*(t < 4 ? 2*u + (t >> 1) : 8 + u) + 2*c + (t & 1);
}
__host__ __device__ __forceinline__ int brow_dim(int T, int row) {
  const int half = row >> 3, g = row & 7;
  return T < 3 ? slot_dim(g, 2*T + half) : T > 3 ? slot_dim(g + 8, 2*(T - 4) + half) : slot_dim(g + 8*half, 6);
}

#define TRACE(k, i)

struct Maps { CUtensorMap wq, wk, wv, wo, x120, x64, ax, aw, ao, oa; };

#define PREP_PF 0
constexpr int PR_STAGE = 32768 + 28672, PR_BAR = 3*PR_STAGE, PR_SMEM = PR_BAR + 64;

__global__ void __launch_bounds__(256, 1) prep_kernel(const __grid_constant__ Maps mp, const bf16* __restrict__ mem0) {
  extern __shared__ __align__(1024) uint8_t smem[];
  const uint32_t sb = smem_u32(smem);
  const int tid = threadIdx.x, b = blockIdx.x;
  if (tid == 0) TRACE(0, 0);
  asm volatile("griddepcontrol.launch_dependents;");
  if (b >= 128) {
    const int t = (b - 128)*256 + tid;
    if (t < F_COUNT) g_flag[t*32] = 0;
    #pragma unroll 1
    for (int i = t; i < 5*4*REP*128; i += 1024) {
      uint4 v = make_uint4(0, 0, 0, 0);
      if (i < 4*REP*128 && (i & (REP*128 - 1)) < 128) {
        const int r = i / (REP*128), p = i & 127, rho = (p >> 6)*8 + ((p >> 2) & 7), q = 2*(p & 3) + ((p >> 5) & 1);
        const unsigned short* m = (const unsigned short*)mem0 + q*448 + r*112;
        v = make_uint4(*(const uint32_t*)(m + slot_dim(rho, 0)), *(const uint32_t*)(m + slot_dim(rho, 2)), *(const uint32_t*)(m + slot_dim(rho, 4)), m[slot_dim(rho, 6)] | 0x41800000u);
      }
      g_MACC[i < 4*REP*128 ? SSTR_(i / (REP*128)) + ((i >> 7) & (REP - 1))*RSTR + (i & 127) : i] = v;
    }
    return;
  }
  const int mat = b >> 6, h = (b >> 2) & 15, qm = (b >> 1) & 1, qn = b & 1;
  const int warp = __shfl_sync(0xffffffffu, tid >> 5, 0), wg = warp >> 2, lane = tid & 31;
  const uint32_t bar = sb + PR_BAR;
  auto issue = [&](int kc) {
    const uint32_t st = sb + (kc % 3)*PR_STAGE, br = bar + (kc % 3)*8;
    mbar_expect_tx(br, (4 - qm)*8192 + 28672);
    tma2d(st + 32768, mat ? &mp.wv : &mp.wk, h*256 + kc*64, qn*224, br);
    #pragma unroll 1
    for (int i = 0; i < 4 - qm; i++) { const int e = h*256 + kc*64, j = (4*qm + i)*64; tma2d(st + i*8192, mat ? &mp.wo : &mp.wq, mat ? j : e, mat ? e : j, br); }
  };
  if (warp == 0 && elect()) { mbar_init(bar, 1); mbar_init(bar + 8, 1); mbar_init(bar + 16, 1); fence_async_smem(); }
  float acc[2][112];
  #pragma unroll 1
  for (int kc = -1; kc < 4; kc++) {
    if (kc >= 0) {
      const int sg = kc == 3 ? 0 : kc;
      const uint32_t al = wg_lo(sb + sg*PR_STAGE + wg*16384, mat ? 8192 : 16), bl = wg_lo(sb + sg*PR_STAGE + 32768, 16);
      mbar_wait(bar + sg*8, kc == 3);
      if (mat) { wg_fence(); static_for<0, 8>([&](auto j) { wg_ss224<1, DH_SW, (j.value & 1)*8192 + (j.value >> 1)*2048, 0, DH_SW, (j.value >> 1)*32>(acc[j.value & 1], al, bl, kc | (j.value >> 1)); }); wg_commit(); }
      else { wg_fence(); static_for<0, 8>([&](auto j) { wg_ss224<0, DH_SW, (j.value & 1)*8192 + (j.value >> 1)*32, 0, DH_SW, (j.value >> 1)*32>(acc[j.value & 1], al, bl, kc | (j.value >> 1)); }); wg_commit(); }
    }
    if (kc <= 0) {
      if (kc == 0) { wg_wait<0>(); __syncthreads(); }
      if (warp == 0 && elect()) {
        #pragma unroll 1
        for (int k = kc ? 0 : 3; k < 4 + kc; k++) issue(k);
        if (kc && PREP_PF) {
          tma2d_pf(mat ? &mp.wv : &mp.wk, h*256 + 192, qn*224);
          #pragma unroll 1
          for (int i = 0; i < 4 - qm; i++) { const int e = h*256 + 192, j = (4*qm + i)*64; tma2d_pf(mat ? &mp.wo : &mp.wq, mat ? j : e, mat ? e : j); }
        }
      }
      if (kc) __syncthreads();
      __syncwarp();
    }
  }
  wg_wait<0>();
  if (tid == 0) TRACE(0, 2);
  const int g = lane >> 2, odd = g & 1;
  const float sc = mat ? 1.0f : 0.0625f*1.4426950408889634f;
  #pragma unroll
  for (int i = 0; i < 2; i++) {
    wg_pin(acc[i]);
    const int tt = (4*qm + 2*wg + i)*4 + (warp & 3), r = tt / 7, t = tt - 7*r;
    if (tt < 28) {
      const bool sw = mat && t < 6;
      const int n = 2*t + odd, u = n < 8 ? n >> 1 : n - 8, v = n < 8 ? n & 1 : 2;
      const int T = !mat ? tt : 7*r + (sw ? 4*(u >> 1) + v : 3), l = !mat ? lane : 4*(4*(sw ? u & 1 : odd) + (g >> 1)) + (lane & 3);
      uint4* dst = g_WF + ((size_t)((mat*16 + h)*28 + T)*28 + 14*qn)*32 + l;
      #pragma unroll
      for (int K = 0; K < 14; K++) {
        const float* a = &acc[i][8*K];
        const uint32_t lo0 = pack2(a[0]*sc, a[1]*sc), hi0 = pack2(a[2]*sc, a[3]*sc), lo1 = pack2(a[4]*sc, a[5]*sc), hi1 = pack2(a[6]*sc, a[7]*sc);
        const uint32_t r0 = __shfl_xor_sync(0xffffffffu, odd ? lo0 : hi0, sw ? 4 : 0), r1 = __shfl_xor_sync(0xffffffffu, odd ? lo1 : hi1, sw ? 4 : 0);
        dst[K*32] = make_uint4(odd ? r0 : lo0, odd ? hi0 : r0, odd ? r1 : lo1, odd ? hi1 : r1);
      }
    }
  }
  if (tid == 0) TRACE(0, 3);
}

#define GAP_K 2
#define G_EARLY 2
#define XLATE 0
#define YFIRST 0
#define UWAIT 1
#define SM_HI 122880
#define HSH 0
#define EF 3
#define GPRE 7
constexpr int XP = 240;
constexpr int XS = 32*XP;
constexpr int ST_BYTES = 4*XS + 14336;
constexpr int SM_X = 0;
constexpr int SM_GU = 12*XS;
constexpr int SM_M = SM_HI;
constexpr int SM_WP = SM_M + 8192;
constexpr int SM_GM = SM_WP + 8192;
constexpr int SM_PK = SM_GM + 8192;
constexpr int SM_CT = SM_PK + 7168;
constexpr int SM_SMM = SM_CT + 9216;
constexpr int SM_SMX = SM_SMM + 2048;
constexpr int SM_BX = SM_SMX + 2048;
constexpr int SM_BAR = SM_BX + 1024;
constexpr int REC_SMEM = SM_BAR + 128;
constexpr int BAR_M = 0, BAR_ST = 32, BAR_SMX = 64, BAR_SMM = 72, SM_T = SM_BAR + 120;

#define M_LOAD(a) _Pragma("unroll") for (int k_ = 0; k_ < 7; k_++) X[k_] = lds64v((a) + k_*256)
#define FENCE(i) asm volatile("{.reg .pred p; setp.eq.u32 p, %0, %1; @p trap;}" :: "r"(h), "n"((i) + 1000) : "memory")

template<int ROLE>
__device__ __forceinline__ void rec_warp(const uint32_t sb, const int lane, const int w, const int h, const int r,
                                         const CUtensorMap* xmap, const int delay, const int ring) {
  constexpr bool P = ROLE < 2;
  const uint32_t bar = sb + SM_BAR;
  const int sl = (r + 1 + w) & 3, hf = w & 1;
  uint32_t l16 = opaque(sb + lane*16, lane);
  const uint32_t mb = opaque(sb + SM_M + lane*8, lane);
  auto prefetch = [&](int s) {
    const uint32_t st = sb + SM_GU + (s & 1)*14336, b = bar + BAR_ST + (s & 3)*8;
    mbar_expect_tx(b, ST_BYTES);
    (EF & 1 ? bulk_g2s_last : bulk_g2s)(st, g_GF + ((size_t)((s & ring)*16 + h)*28 + 7*r)*64, 7168, b);
    bulk_g2s(st + 7168, g_UF + ((size_t)((s & ring)*16 + h)*28 + 7*r)*64, 7168, b);
    tma2d_mc(sb + SM_X + ((s % 3)*4 + r)*XS, xmap, r*112, s*32, b);
  };
  auto gu_wait = [&](int tile) {
    const int ln = (l16 >> 4) & 3, f = F_GU + (((ln >> 1)*16 + h)*28 + 7*r + (ln & 1)*6) / 16;
    int i = 0;
    while (__any_sync(0xffffffffu, (int)flag_get(f) <= tile) && ++i < SPIN_MAX) {}
  };
  uint4 W[7][7];
  {
    const uint4* src = g_WF + ((size_t)(((P ? 0 : 16) + h)*28 + 7*(P ? sl : r))*28 + 7*(P ? r : sl))*32 + lane;
    #pragma unroll
    for (int t = 0; t < 7; t++)
      #pragma unroll
      for (int k = 0; k < 7; k++) { W[t][k] = ldcg4(src + (t*28 + k)*32); if (ROLE == 0 && t == 6) sts128(l16 + SM_PK + (hf*7 + k)*512, W[t][k]); }
  }
  if (ROLE == 1 && w == 1 && lane == 0) TRACE(2, 1);
  if (ROLE == 1 && w == 0) {
    gu_wait(0);
    if (elect()) {
      #pragma unroll 1
      for (int i = 0; i < 1; i++) prefetch(i);
    }
    __syncwarp();
  }
  uint4* redp = g_MACC + 4*REP*128 + SSTR_(r) + ((h >> HSH) & (REP - 1))*RSTR + hf*64 + lane;
  if (ROLE == 0) {
    sts128(l16 + SM_CT + hf*512, make_uint4(sb + SM_WP + (l16 & 0x100)*8 + (l16 & 0xf0) + hf*1024,
      (l16 & 0x80) ? sb + SM_WP + 1792 + ((l16 & 0x100) >> 1) + (l16 & 0x70) : sb + SM_WP + (l16 & 0x100)*8 + 768 + hf*128 + (l16 & 0x70),
      (l16 >> 1) & 0x18, ((l16 >> 1) & 0x18) + 4));
  }
  uint32_t rb[3];
  #pragma unroll
  for (int d = 0; d < 3; d++) rb[d] = mapa(sb, (d + r + 1) & 3) - sb;
  if (!P) {
    const uint32_t o = sb + SM_SMM + w*128 + lane*4, b = bar + BAR_SMM, o2 = sb + SM_SMX + w*256 + lane*8, b2 = bar + BAR_SMX;
    sts128(l16 + SM_CT + 1024 + w*1024, make_uint4(rb[0] + o, rb[0] + b, rb[1] + o + 512, rb[1] + b));
    sts128(l16 + SM_CT + 1536 + w*1024, make_uint4(rb[2] + o + 1024, rb[2] + b, o + 1536, 8 + w));
    const uint32_t ml = sb + SM_M + 6144 + (l16 & 0x30)*4 + hf*32 + ((l16 & 0xc0) >> 3);
    sts128(l16 + SM_CT + 7168 + w*512, make_uint4(ml + (w >> 1)*512 + (l16 & 0x100), ml + 1024 + (w >> 1)*256 + ((l16 & 0x100) >> 6), ml + 1536 + (w >> 1)*4 + ((l16 & 0x100) >> 7), 0));
    if (ROLE == 2) {
      sts128(l16 + SM_CT + 5120 + w*1024, make_uint4(rb[0] + o2, rb[0] + b2, rb[1] + o2 + 512, rb[1] + b2));
      sts128(l16 + SM_CT + 5632 + w*1024, make_uint4(rb[2] + o2 + 1024, rb[2] + b2, o2 + 1536, 0));
    }
  }
  uint32_t par = opaque(0, lane);
  uint32_t tred = clk() - 100000;
  uint32_t G[7][4];
  auto load_g = [&](int s) {
    mbar_wait(bar + BAR_ST + (s & 3)*8, (s >> 2) & 1);
    #pragma unroll
    for (int k = 0; k < GPRE; k++) ldsm4t(G[k], l16 + SM_GU + (s & 1)*14336 + w*512 + k*1024);
  };
  if (ROLE == 2 && G_EARLY != 2) load_g(0);
  #pragma unroll 1
  for (int s = 0; s < NSEG; s++) {
    asm volatile("" : "+r"(l16));
    const int stg = s & 3;
    const uint32_t st = l16 + SM_GU + (s & 1)*14336;
    if (P) {
      if (ROLE == 0) {
        #pragma unroll
        for (int k = 0; k < 7; k++) W[6][k] = lds128v(l16 + SM_PK + (hf*7 + k)*512);
      }
      if (w == 0 || w == 3) bar_arrive(7, 96);
      bar_sync(1, 256);
      {
        uint2 X[7]; M_LOAD(mb + 6144);
        float acc[7][4];
        #pragma unroll
        for (int k = 0; k < 7; k++)
          #pragma unroll
          for (int t = 0; t < 7; t++) {
            if (ROLE == 1 && k == GAP_K && t == 0) FENCE(0);
            if (k == 0) mma16z(acc[t], W[t][k].x, W[t][k].y, W[t][k].z, W[t][k].w, X[k].x, X[k].y); else mma16(acc[t], W[t][k].x, W[t][k].y, W[t][k].z, W[t][k].w, X[k].x, X[k].y); }
        const uint32_t gmw = l16 + SM_GM + w*2048;
        #pragma unroll
        for (int t = 0; t < 6; t += 2) stsm4(gmw + t*256, pack2(acc[t][0], acc[t][1]), pack2(acc[t+1][0], acc[t+1][1]), pack2(acc[t][2], acc[t][3]), pack2(acc[t+1][2], acc[t+1][3]));
        const uint32_t lo = pack2(acc[6][0], acc[6][1]), hi = pack2(acc[6][2], acc[6][3]);
        stsm4(gmw + 1536, lo, lo, hi, hi);
        bar_arrive(8 + w, 64);
      }
      if (ROLE == 0) mbar_wait(bar + BAR_ST + stg*8, (s >> 2) & 1);
      const int ln = (l16 >> 4) & 31;
      if (ROLE == 0) {
        const uint4 ct = lds128v(l16 + SM_CT + hf*512);
        if (UWAIT) mbar_wait(bar + BAR_SMX, par);
        uint4 U[4][2];
        #pragma unroll
        for (int k = 0; k < 2; k++) { uint4 v = lds128v(st + 7168 + 3072 + k*512); U[3][k] = make_uint4(hf ? v.y : v.x, 0x3f803f80u, hf ? v.w : v.z, 0x3f803f80u); }
        #pragma unroll
        for (int a = 0; a < 3; a++) { U[a][0] = lds128v(st + 7168 + hf*4096 + a*1024); U[a][1] = lds128v(st + 7168 + hf*4096 + a*1024 + 512); }
        asm volatile("" : "+r"(U[3][0].x), "+r"(U[3][0].y), "+r"(U[3][0].z), "+r"(U[3][0].w), "+r"(U[3][1].x), "+r"(U[3][1].y), "+r"(U[3][1].z), "+r"(U[3][1].w));
        mbar_wait(bar + BAR_SMM, par);
        float s0, s1;
        {
          uint32_t p[4][4], t[4];
          #pragma unroll
          for (int i = 0; i < 4; i++) ldsm4t(p[i], l16 + SM_SMM + i*512);
          #pragma unroll
          for (int i = 0; i < 4; i++) t[i] = hadd2(hadd2(p[i][0], p[i][1]), hadd2(p[i][2], p[i][3]));
          s0 = (bflo(t[0]) + bflo(t[1])) + (bflo(t[2]) + bflo(t[3])); s1 = (bfhi(t[0]) + bfhi(t[1])) + (bfhi(t[2]) + bfhi(t[3]));
        }
        float cm = fmaxf(s0, s1);
        const float m1 = __shfl_xor_sync(0xffffffffu, cm, 1), m2 = __shfl_xor_sync(0xffffffffu, cm, 2), m3 = __shfl_xor_sync(0xffffffffu, cm, 3);
        FENCE(2);
        bar_sync(13, 96);
        const float cx = __uint_as_float(lds32(mb - SM_M + SM_BX + 512));
        const uint4 bx = lds128v(l16 + SM_BX);
        float ox[4][4];
        #pragma unroll
        for (int a = 0; a < 4; a++) mma16z(ox[a], U[a][0].x, U[a][0].y, U[a][0].z, U[a][0].w, bx.x, bx.y);
        #pragma unroll
        for (int a = 0; a < 4; a++) mma16(ox[a], U[a][1].x, U[a][1].y, U[a][1].z, U[a][1].w, bx.z, bx.w);
        bar_sync(4, 192);
        uint32_t Wf[4][2][4];
        #pragma unroll
        for (int i = 0; i < 2; i++) {
          ldsm4(Wf[3][i], ct.y + i*4096);
          #pragma unroll
          for (int a = 0; a < 3; a++) ldsm4(Wf[a][i], ct.x + a*256 + i*4096);
        }
        cm = fmaxf(fmaxf(fmaxf(cm, cx), m1), fmaxf(m2, m3));
        const float e0 = ex2(s0 - cm), e1 = ex2(s1 - cm), f = ex2(cx - cm);
        const uint32_t bm = pack2(e0, e1);
        const float f0 = __shfl_sync(0xffffffffu, f, ct.z), f1 = __shfl_sync(0xffffffffu, f, ct.w);
        float o[4][4];
        #pragma unroll
        for (int a = 3; a >= 0; a--) mma16z(o[a], Wf[a][0][0], Wf[a][0][1], Wf[a][0][2], Wf[a][0][3], bm, bm);
        #pragma unroll
        for (int a = 3; a >= 0; a--) mma16(o[a], Wf[a][1][0], Wf[a][1][1], Wf[a][1][2], Wf[a][1][3], bm, bm);
        #pragma unroll
        for (int a = 3; a >= 0; a--) { o[a][0] = fmaf(ox[a][0], f0, o[a][0]); o[a][1] = fmaf(ox[a][1], f1, o[a][1]); o[a][2] = fmaf(ox[a][2], f0, o[a][2]); o[a][3] = fmaf(ox[a][3], f1, o[a][3]); }
        const float i0 = rcp(o[3][2]), i1 = rcp(o[3][3]);
        red_bf16x8(redp, pack2(o[0][0]*i0, o[0][2]*i0), pack2(o[1][0]*i0, o[1][2]*i0), pack2(o[2][0]*i0, o[2][2]*i0), pack2(o[3][0]*i0, 1.0f));
        red_bf16x8(redp + 32, pack2(o[0][1]*i1, o[0][3]*i1), pack2(o[1][1]*i1, o[1][3]*i1), pack2(o[2][1]*i1, o[2][3]*i1), pack2(o[3][1]*i1, 1.0f));
        sts32(sb + SM_T, clk());
        bar_arrive(5, 192);
        bar_arrive(6, 128);
        FENCE(1);
        redp += 4*REP*128;
        asm volatile("" : "+l"(redp));
        uint2* wd = g_WD + (((s & ring)*16 + h)*28 + 7*r)*32 + ln;
        #pragma unroll
        for (int a = 0; a < 4; a++) {
          const uint32_t lo = hadd2(hadd2(Wf[a][0][0], Wf[a][0][2]), hadd2(Wf[a][1][0], Wf[a][1][2]));
          if (a < 3) wd[(hf*4 + a)*32] = make_uint2(lo, hadd2(hadd2(Wf[a][0][1], Wf[a][0][3]), hadd2(Wf[a][1][1], Wf[a][1][3])));
          else ((uint32_t*)(wd + 96))[hf] = lo;
        }
      } else {
        if (w == 1) {
          const uint32_t l8 = mb - SM_M + SM_SMX;
          mbar_wait(bar + BAR_SMX, par);
          float sx[8];
          #pragma unroll
          for (int i = 0; i < 2; i++) {
            const uint2 p0 = lds64(l8 + i*256), p1 = lds64(l8 + i*256 + 512), p2 = lds64(l8 + i*256 + 1024), p3 = lds64(l8 + i*256 + 1536);
            const uint32_t a0 = hadd2(p0.x, p1.x), a1 = hadd2(p2.x, p3.x), b0 = hadd2(p0.y, p1.y), b1 = hadd2(p2.y, p3.y);
            sx[4*i] = bflo(a0) + bflo(a1); sx[4*i+1] = bfhi(a0) + bfhi(a1); sx[4*i+2] = bflo(b0) + bflo(b1); sx[4*i+3] = bfhi(b0) + bfhi(b1);
          }
          const float cx = quad_max(fmaxf(fmaxf(fmaxf(sx[0], sx[1]), fmaxf(sx[2], sx[3])), fmaxf(fmaxf(sx[4], sx[5]), fmaxf(sx[6], sx[7]))));
          sts32(mb - SM_M + SM_BX + 512, __float_as_uint(cx));
          sts128(l16 + SM_BX, make_uint4(pack2(ex2(sx[0] - cx), ex2(sx[1] - cx)), pack2(ex2(sx[2] - cx), ex2(sx[3] - cx)), pack2(ex2(sx[4] - cx), ex2(sx[5] - cx)), pack2(ex2(sx[6] - cx), ex2(sx[7] - cx))));
          bar_arrive(13, 96);
        } else {
          if (lane == 0) TRACE(2, 2 + s);
          if (!(s & 1) && s + 2 < NSEG) gu_wait((s + 2) >> 1);
          if (((s & 1) || s > NSEG - 4) && ln == 0) flag_set(F_REC + h*4 + r, s);
          __syncwarp();
        }
        mbar_wait(bar + BAR_ST + stg*8, (s >> 2) & 1);
        bar_sync(6, 128);
        if (w == 1) {
          g_MACC[(s + 5)*4*REP*128 + (h*4 + r)*(REP*8) + (ln & (REP*8 - 1))] = make_uint4(0, 0, 0, 0);
          if (elect()) { mbar_expect_tx(bar + BAR_SMM, 1536); mbar_expect_tx(bar + BAR_SMX, 1536); }
        }
      }
      {
        uint4* dst = g_SX + ((s & ring)*64 + h*4 + r)*128 + ln;
        const uint32_t xs = sb + SM_X + ((s % 3)*4 + sl)*XS + (ln & 15)*XP + (ln >> 4)*16;
        const uint32_t lb = sb + (l16 & 0x70) + (l16 & 0x80)*2 + ((l16 & 0x100) >> 1);
        float S[2][4];
        if (ROLE == 0 && w == 3) {
          float T[6][4];
          uint32_t b[4];
          #pragma unroll
          for (int k = 0; k < 7; k++) {
            uint32_t a0[4], a1[4], g0[4], g1[4];
            if (!(k & 1)) ldsm4t(b, lb + SM_GM + 6144 + k*256);
            ldsm4(a0, xs + k*32); ldsm4(a1, xs + 16*XP + k*32);
            ldsm4t(g0, lb + SM_GU + (s & 1)*14336 + k*1024); ldsm4t(g1, lb + SM_GU + (s & 1)*14336 + k*1024 + 512);
            auto mm = [&](float (&d)[4], const uint32_t (&a)[4], uint32_t b0, uint32_t b1) { if (k == 0) mma16z(d, a[0], a[1], a[2], a[3], b0, b1); else mma16(d, a[0], a[1], a[2], a[3], b0, b1); };
            mm(S[0], a0, b[(k & 1)*2], b[(k & 1)*2 + 1]); mm(S[1], a1, b[(k & 1)*2], b[(k & 1)*2 + 1]);
            mm(T[0], a0, g0[0], g0[1]); mm(T[1], a0, g0[2], g0[3]); mm(T[2], a1, g0[0], g0[1]); mm(T[3], a1, g0[2], g0[3]); mm(T[4], a1, g1[0], g1[1]); mm(T[5], a1, g1[2], g1[3]);
          }
          #pragma unroll
          for (int i = 0; i < 3; i++) dst[(1 + i)*32] = make_uint4(pack2(T[2*i][0], T[2*i][1]), pack2(T[2*i+1][0], T[2*i+1][1]), pack2(T[2*i][2], T[2*i][3]), pack2(T[2*i+1][2], T[2*i+1][3]));
        } else {
          #pragma unroll
          for (int k0 = 0; k0 < 7; k0 += 4) {
            uint32_t a[4][2][4], b[2][4];
            #pragma unroll
            for (int k = k0; k < k0 + 4 && k < 7; k++) { if (!(k & 1)) ldsm4t(b[(k >> 1) & 1], lb + SM_GM + w*2048 + k*256); ldsm4(a[k & 3][0], xs + k*32); ldsm4(a[k & 3][1], xs + 16*XP + k*32); }
            if (k0 == 0) FENCE(8); else FENCE(9);
            #pragma unroll
            for (int k = k0; k < k0 + 4 && k < 7; k++)
              #pragma unroll
              for (int i = 0; i < 2; i++) { const uint32_t (&q)[4] = a[k & 3][i]; const uint32_t b0 = b[(k >> 1) & 1][(k & 1)*2], b1 = b[(k >> 1) & 1][(k & 1)*2 + 1];
                if (k == 0) mma16z(S[i], q[0], q[1], q[2], q[3], b0, b1); else mma16(S[i], q[0], q[1], q[2], q[3], b0, b1); }
          }
        }
        const uint4 v = make_uint4(pack2(S[0][0], S[0][1]), pack2(S[0][2], S[0][3]), pack2(S[1][0], S[1][1]), pack2(S[1][2], S[1][3]));
        if (ROLE == 0 || w == 1) { sts128(l16 + SM_GM + w*2048, v); bar_arrive(2, 128); }
        else { bar_sync(2, 128); dst[0] = hadd8(hadd8(v, lds128(l16 + SM_GM + 2048)), hadd8(lds128(l16 + SM_GM + 4096), lds128(l16 + SM_GM + 6144))); }
      }
    } else {
      uint2 Y[7];
      {
        const uint4* ga = g_MACC + s*4*REP*128 + SSTR_(r) + w*32 + ((l16 >> 4) & 31);
        const uint4 mc = lds128v(l16 + SM_CT + 7168 + w*512);
        const uint32_t m0 = mc.x, m1 = mc.y, m2 = mc.z;
        asm volatile("" : "+l"(ga));
        while ((int)(clk() - tred) < (delay & 0xffff)) {}
        uint4 v, u[REP]; int n = 0;
        if (ROLE == 2 && G_EARLY == 2) {
          #pragma unroll
          for (int i = 0; i < REP; i++) u[i] = ld_relaxed4(ga + i*RSTR);
          load_g(s);
        }
        do {
          if (ROLE == 2) asm volatile("" : "+r"(n));
          if (ROLE != 2 || G_EARLY != 2 || n) {
            #pragma unroll
            for (int i = 0; i < REP; i++) u[i] = ld_relaxed4(ga + i*RSTR);
          }
          ++n;
          v = REP == 1 ? u[0] : hadd8(u[0], u[REP > 1]);
          if (REP == 4) v = hadd8(v, hadd8(u[REP-2], u[REP-1]));
          sts64(m0, v.x, v.y); sts32(m1, v.z); sts16(m2, v.w);
        } while (__any_sync(0xffffffffu, v.w < 0x41800000u) && n < SPIN_MAX);
        if (ROLE == 2 && YFIRST) {
          bar_sync(1, 256);
          #pragma unroll
          for (int k = 0; k < 7; k++) Y[k] = lds64v(mb + 6144 + k*256);
          #pragma unroll
          for (int k = GPRE; k < 7; k++) ldsm4t(G[k], st + w*512 + k*1024);
        } else if (YFIRST && w == 3) bar_sync(1, 256);
        else bar_arrive(1, 256);
        tred = n > 1 ? ring >> 16 : 0;
        if (!YFIRST || (ROLE == 3 && w == 3)) fence_async_smem();
        if (!YFIRST) {
          if (ROLE == 2) {
            #pragma unroll
            for (int k = GPRE; k < 7; k++) ldsm4t(G[k], st + w*512 + k*1024);
          }
          bar_sync(3, 128);
        }
        if (ROLE == 3 && w == 3) {
          if (elect()) {
            #pragma unroll
            for (int d = 0; d < 3; d++) bulk_s2s(rb[d] + sb + SM_M + (2 - d)*2048, sb + SM_M + 6144, 1792, rb[d] + bar + BAR_M + (2 - d)*8);
          }
          bar_sync(7, 96);
          if (s + 1 < NSEG && elect()) prefetch(s + 1);
          __syncwarp();
        }
      }
      if (ROLE == 2) {
        if (!YFIRST) {
          #pragma unroll
          for (int k = 0; k < 7; k++) Y[k] = lds64v(mb + 6144 + k*256);
        }
        FENCE(4);
        float S[7][4];
        #pragma unroll
        for (int k = 0; k < 7; k++) mma16z(S[k], G[k][0], G[k][1], G[k][2], G[k][3], Y[k].x, Y[k].y);
        FENCE(5);
        const uint4 c0 = lds128v(l16 + SM_CT + 5120 + w*1024), c1 = lds128v(l16 + SM_CT + 5632 + w*1024);
        float t[4];
        #pragma unroll
        for (int i = 0; i < 4; i++) t[i] = ((S[0][i] + S[1][i]) + (S[2][i] + S[3][i])) + ((S[4][i] + S[5][i]) + S[6][i]);
        const uint32_t v0 = movm(pack2(t[0], t[1])), v1 = movm(pack2(t[2], t[3]));
        st_async2(c0.x, v0, v1, c0.y); st_async2(c0.z, v0, v1, c0.w); st_async2(c1.x, v0, v1, c1.y);
        sts64(c1.z, v0, v1);
        mbar_arrive(bar + BAR_SMX);
      }
      uint2 X[7];
      {
        const uint4 c0 = lds128v(l16 + SM_CT + 1024 + w*1024), c1 = lds128v(l16 + SM_CT + 1536 + w*1024);
        uint32_t a[4][4];
        if (ROLE == 3 || !XLATE) { if (ROLE == 2 || w == 2) mbar_wait(bar + BAR_M + w*8, par); M_LOAD(mb + w*2048); }
        bar_sync(c1.w, 64);
        #pragma unroll
        for (int k2 = 0; k2 < 4; k2++) ldsm4t(a[k2], l16 + SM_GM + w*2048 + k2*512);
        if (ROLE == 2 && XLATE) { mbar_wait(bar + BAR_M + w*8, par); M_LOAD(mb + w*2048); }
        float S[7][4];
        #pragma unroll
        for (int k = 0; k < 7; k++) mma16z(S[k], a[k >> 1][0], a[k >> 1][1], a[k >> 1][2], a[k >> 1][3], X[k].x, X[k].y);
        const uint32_t v = pack2(((S[0][0] + S[1][2]) + (S[2][0] + S[3][2])) + ((S[4][0] + S[5][2]) + S[6][0]), ((S[0][1] + S[1][3]) + (S[2][1] + S[3][3])) + ((S[4][1] + S[5][3]) + S[6][1]));
        st_async1(c0.x, v, c0.y); st_async1(c0.z, v, c0.w); st_async1(c1.x, v, c1.y);
        sts32(c1.z, v);
        mbar_arrive(bar + BAR_SMM);
        FENCE(7);
      }
      float acc[7][4];
      #pragma unroll
      for (int k = 0; k < 7; k++)
        #pragma unroll
        for (int t = 0; t < 7; t++) { if (k == 0) mma16z(acc[t], W[t][k].x, W[t][k].y, W[t][k].z, W[t][k].w, X[k].x, X[k].y); else mma16(acc[t], W[t][k].x, W[t][k].y, W[t][k].z, W[t][k].w, X[k].x, X[k].y); }
      #pragma unroll
      for (int t = 0; t < 6; t += 2) stsm4(l16 + SM_WP + w*2048 + t*256, pack2(acc[t][0], acc[t][1]), pack2(acc[t][2], acc[t][3]), pack2(acc[t+1][0], acc[t+1][1]), pack2(acc[t+1][2], acc[t+1][3]));
      stsm2(l16 + SM_WP + w*2048 + 1536, pack2(acc[6][0], acc[6][1]), pack2(acc[6][2], acc[6][3]));
      bar_arrive(4, 192);
      if (w != 3 && elect()) mbar_expect_tx(bar + BAR_M + w*8, 1792);
      if (ROLE == 2 && G_EARLY == 1) load_g(s < NSEG - 1 ? s + 1 : s);
      bar_sync(5, 192);
      tred += lds32(sb + SM_T);
      if (ROLE == 2 && !G_EARLY) load_g(s < NSEG - 1 ? s + 1 : s);
    }
    par ^= 1;
  }
  if (P) {
    bar_sync(12, 128);
    if (ROLE == 1 && w == 1 && elect()) { flag_set(F_REC + h*4 + r, NSEG); TRACE(2, 66); }
  }
}

__device__ __forceinline__ void rec_init(const uint32_t sb, const int tid) {
  const uint32_t bar = sb + SM_BAR;
  if (tid == 0) {
    for (int i = 0; i < 8; i++) mbar_init(bar + i*8, 1);
    mbar_init(bar + BAR_SMX, 65); mbar_init(bar + BAR_SMM, 129);
    for (int i = 0; i < 3; i++) mbar_expect_tx(bar + BAR_M + i*8, 1792);
    mbar_expect_tx(bar + BAR_SMX, 1536); mbar_expect_tx(bar + BAR_SMM, 1536);
  }
  if (tid < 128) sts32(sb + SM_WP + (tid >> 6)*4096 + 1792 + (tid & 63)*4, tid < 32 ? 0x3f803f80u : 0u);
}

#define KSPLIT 4
#define KTURN 16
constexpr int GM_W = 0, GM_X = 114688, GM_BAR = 229376, GM_SMEM = GM_BAR + 384;

__device__ __forceinline__ void gemm_wg(const uint32_t sb, const int cta, const int warp, const int lane) {
  const uint32_t bar = sb + GM_BAR;
  const int wg = warp >> 2, w = warp & 3;
  const int u_rs = 4*cta + 2*wg;
  uint4 W[28];
  {
    const uint4* src = g_WF + (size_t)(u_rs*4 + w)*28*32 + lane;
    const uint32_t dst = sb + GM_W + wg*57344 + (lane >> 4)*1024 + (2*w + ((lane >> 3) & 1))*128 + (lane & 7)*16;
    #pragma unroll
    for (int k = 0; k < 28; k++) W[k] = ldcg4(src + (4*28 + k)*32);
    #pragma unroll
    for (int k = 0; k < 28; k++) { stsm4(dst + k*2048, W[k].x, W[k].y, W[k].z, W[k].w); W[k] = ldcg4(src + k*32); }
  }
  fence_async_smem();
  bar_sync(2 + wg, 128);
  if (warp == 0 && lane == 0) TRACE(1, 1);
  const uint32_t dw = wg_lo(sb + GM_W + wg*57344, 1024);
  const uint32_t rempty = mapa(bar + 16, lane & 3);
  const bool isg = cta < 28;
  uint32_t* dst = (uint32_t*)((isg ? g_GF : g_UF) + ((u_rs % 112)*4 + w)*64) + (isg ? lane : lane*4);
  float acc[2][32];
  uint32_t pk[2][16];
  #pragma unroll 1
  for (int t = 0; t <= 32; t++) {
    const uint32_t dx = wg_lo(sb + GM_X + (t & 1)*57344, 16);
    auto step = [&](auto k) {
      wg_ss64<0, DH_NS, k.value*2048, 0, DH_SW, (k.value >> 2)*8192 + (k.value & 3)*32>(acc[1], dw, dx, k.value > 0);
      wg_rs64<0, DH_SW, (k.value >> 2)*8192 + (k.value & 3)*32, (k.value > 0)>(acc[0], W[k.value], dx);
    };
    if (t < 32) {
      if (wg | t) bar_sync(4 + wg, 256);
      mbar_wait(bar + (t & 1)*8, (t >> 1) & 1);
      wg_fence();
      static_for<0, KSPLIT>(step);
      wg_commit();
    }
    if (t > 0) {
      if (isg) {
        #pragma unroll
        for (int i = 0; i < 32; i++) dst[(i >> 4)*1024 + ((i >> 3) & 1)*(16*28*256) + ((i >> 2) & 1)*128 + ((i & 1)*2 + ((i >> 1) & 1))*32] = pk[i >> 4][i & 15];
      } else {
        #pragma unroll
        for (int i = 0; i < 8; i++) ((uint4*)dst)[(i >> 2)*256 + ((i >> 1) & 1)*(16*28*64) + (i & 1)*32] = make_uint4(pk[i >> 2][4*(i & 3)], pk[i >> 2][4*(i & 3) + 1], pk[i >> 2][4*(i & 3) + 2], pk[i >> 2][4*(i & 3) + 3]);
      }
      dst += 2*16*28*256;
      __syncwarp();
      if (lane == 0) mbar_arrive(bar + 32 + ((t - 1) & 1)*8);
    }
    if (t < 32) {
      wg_fence();
      static_for<KSPLIT, KTURN>(step);
      if (t + wg < 32) bar_arrive(5 - wg, 256);
      static_for<KTURN, 28>(step);
      wg_commit();
    }
    wg_wait<0>();
    wg_pin(acc[0]); wg_pin(acc[1]);
    if (lane < 4 && t < 30) mbar_arrive_remote(rempty + (t & 1)*8);
    #pragma unroll
    for (int i = 0; i < 32; i++) { pk[i >> 4][i & 15] = pack2(acc[i >> 4][2*(i & 15)], acc[i >> 4][2*(i & 15) + 1]); asm volatile("" : "+r"(pk[i >> 4][i & 15]) :: "memory"); }
  }
}

__device__ __forceinline__ void gemm_aux(const Maps& mp, const uint32_t sb, const int cta, const int lane, const int lead, const int t0, const int t1) {
  const uint32_t bar = sb + GM_BAR;
  const int rank = cta & 3;
  #pragma unroll 1
  for (int t = t0; t < t1; t++) {
    const int need = (t + 2)*2 - lead;
    const bool now = need <= 0 || (int)flag_get(F_REC + cta) >= need;
    #pragma unroll 1
    for (int pass = 0; pass < 2; pass++) {
      if (t < 30 && pass == !now) {
        if (pass) flag_wait(F_REC + cta, need);
        if (t >= 0) mbar_wait(bar + 16 + (t & 1)*8, (t >> 1) & 1);
        if (elect()) {
          const uint32_t b = bar + (t & 1)*8, d = sb + GM_X + (t & 1)*57344 + rank*16384;
          mbar_expect_tx(b, 57344);
          tma2d_mc(d, &mp.x64, rank*128, (t + 2)*64, b);
          if (rank < 3) tma2d_mc(d + 8192, &mp.x64, rank*128 + 64, (t + 2)*64, b);
        }
        __syncwarp();
      }
      if (t >= 0 && !pass) {
        mbar_wait(bar + 32 + (t & 1)*8, (t >> 1) & 1);
        fence_async();
        if (lane == 0) { flag_set(F_GU + cta, t + 1); TRACE(1, 2 + t); }
        __syncwarp();
      }
    }
  }
}

__device__ __forceinline__ void gemm_init(const uint32_t sb) { for (int i = 0; i < 6; i++) mbar_init(sb + GM_BAR + i*8, i < 2 ? 1 : i < 4 ? 32 : 8); }

constexpr int FN_S = 0;
constexpr int FN_P = 65536;
constexpr int FN_R = FN_P + 40960;
constexpr int FN_BAR = 229376 + 128;
constexpr int FN_O = 0, OP = 912;
__device__ __forceinline__ void final_init(const uint32_t sb) { for (int i = 0; i < 32; i++) mbar_init(sb + FN_BAR + i*8, i < 20 ? 1 : 7); }

template<int NT>
__device__ __forceinline__ void final_mma(const uint32_t sb, const int s, const int T0, uint32_t& ph, const int warp, const int tid) {
    constexpr int NS = 12/NT, UB = NT*7168, SLOT = NT*8960;
    const int lane = tid & 31, g = lane >> 2, c = lane & 3;
    const uint32_t bar = sb + FN_BAR;
    float acc[NT][4][4];
    #pragma unroll
    for (int t = 0; t < NT; t++)
      #pragma unroll
      for (int nt = 0; nt < 4; nt++) { acc[t][nt][0] = acc[t][nt][1] = acc[t][nt][2] = acc[t][nt][3] = 0.f; }
    #pragma unroll 2
    for (int h = 0; h < 16; h++) {
      const int sl = h % NS;
      const uint32_t pa = sb + FN_P + h*2560 + lane*16;
      const uint2 p0 = lds64(pa), p1 = lds64(pa + 512);
      const uint4 p2 = lds128(pa + 1024), p3 = lds128(pa + 1536), pm = lds128(pa + 2048);
      mbar_wait(bar + 64 + sl*8, (ph >> sl) & 1);
      ph ^= 1u << sl;
      uint4 U[NT][2]; uint2 Wm[NT];
      #pragma unroll
      for (int t = 0; t < NT; t++) {
        const uint32_t ua = sb + FN_R + sl*SLOT + (warp*NT + t)*1024 + lane*16;
        U[t][0] = lds128v(ua); U[t][1] = lds128v(ua + 512); Wm[t] = lds64v(sb + FN_R + sl*SLOT + UB + (warp*NT + t)*256 + lane*8);
      }
      #pragma unroll
      for (int t = 0; t < NT; t++) {
        mma16(acc[t][0], U[t][0].x, U[t][0].y, U[t][0].z, U[t][0].w, p0.x, p0.y);
        mma16(acc[t][1], U[t][0].x, U[t][0].y, U[t][0].z, U[t][0].w, p1.x, p1.y);
        mma16(acc[t][2], U[t][0].x, U[t][0].y, U[t][0].z, U[t][0].w, p2.x, p2.y);
        mma16(acc[t][3], U[t][0].x, U[t][0].y, U[t][0].z, U[t][0].w, p3.x, p3.y);
      }
      #pragma unroll
      for (int t = 0; t < NT; t++) {
        mma16(acc[t][2], U[t][1].x, U[t][1].y, U[t][1].z, U[t][1].w, p2.z, p2.w);
        mma16(acc[t][3], U[t][1].x, U[t][1].y, U[t][1].z, U[t][1].w, p3.z, p3.w);
        mma8(acc[t][0], Wm[t].x, Wm[t].y, pm.x); mma8(acc[t][1], Wm[t].x, Wm[t].y, pm.y);
      }
      if (h + NS < 16 && lane == 0) mbar_arrive(bar + 160 + sl*8);
      #pragma unroll
      for (int t = 0; t < NT; t++) { mma8(acc[t][2], Wm[t].x, Wm[t].y, pm.z); mma8(acc[t][3], Wm[t].x, Wm[t].y, pm.w); }
    }
    if (tid == 0 && (s == 0 || s == 63)) TRACE(3, 25 + (s & 1)*8);
    #pragma unroll
    for (int t = 0; t < NT; t++) {
      const int T = T0 + t, r = T / 7, tl = T - 7*r;
      const uint32_t a0 = sb + FN_O + 2*c*OP + (r*112 + brow_dim(tl, g))*2;
      if (tl != 3) {
        #pragma unroll
        for (int nt = 0; nt < 4; nt++) { sts32(a0 + nt*8*OP, pack2(acc[t][nt][0], acc[t][nt][2])); sts32(a0 + nt*8*OP + OP, pack2(acc[t][nt][1], acc[t][nt][3])); }
      } else {
        #pragma unroll
        for (int nt = 0; nt < 4; nt++) {
          const uint32_t lo = pack2(acc[t][nt][0], acc[t][nt][1]), hi = pack2(acc[t][nt][2], acc[t][nt][3]);
          sts16(a0 + nt*8*OP, lo); sts16(a0 + nt*8*OP + OP, lo >> 16); sts16(a0 + nt*8*OP + 16, hi); sts16(a0 + nt*8*OP + OP + 16, hi >> 16);
        }
      }
    }
}

__device__ __forceinline__ void final_item(const uint32_t sb, const int s, const int NT, const int part, bf16* __restrict__ out, uint32_t& ph, const int tid) {
  const int warp = __shfl_sync(0xffffffffu, tid >> 5, 0), lane = tid & 31, g = lane >> 2, c = lane & 3;
  const int NS = NT == 4 ? 3 : 12, UB = NT*7168, SLOT = NT*8960;
  const uint32_t bar = sb + FN_BAR;
  if (tid < 64) flag_wait(F_REC + tid, s + 1);
  if (tid == 0 && (s == 0 || s == 63)) TRACE(3, 20 + (s & 1)*8);
  fence_async();
  bar_sync(1, 256);
  if (tid == 0 && (s == 0 || s == 63)) TRACE(3, 21 + (s & 1)*8);
  auto fill = [&](int h, int sl) {
    mbar_expect_tx(bar + 64 + sl*8, SLOT);
    (EF & 2 ? bulk_g2s_last : bulk_g2s)(sb + FN_R + sl*SLOT, g_UF + ((size_t)(s*16 + h)*28 + part*7)*64, UB, bar + 64 + sl*8);
    (EF & 2 ? bulk_g2s_last : bulk_g2s)(sb + FN_R + sl*SLOT + UB, g_WD + ((size_t)(s*16 + h)*28 + part*7)*32, NT*1792, bar + 64 + sl*8);
  };
  const uint4* sp = g_SX + (size_t)(s*16 + warp*2)*512;
  if (elect()) { mbar_expect_tx(bar + warp*8, 8192); (EF & 2 ? bulk_g2s_last : bulk_g2s)(sb + FN_S + warp*8192, sp, 8192, bar + warp*8); }
  __syncwarp();
  #pragma unroll 1
  for (int hh = 0; hh < 2; hh++) {
    const int h = warp*2 + hh;
    uint4 m[4], xs[3][4];
    mbar_wait(bar + warp*8, hh);
    #pragma unroll
    for (int r = 0; r < 4; r++) {
      const uint32_t a = sb + FN_S + warp*8192 + r*2048 + lane*16;
      m[r] = lds128v(a); xs[0][r] = lds128v(a + 512); xs[1][r] = lds128v(a + 1024); xs[2][r] = lds128v(a + 1536);
    }
    if (tid == 0 && (s == 0 || s == 63)) TRACE(3, 22 + hh + (s & 1)*8);
    if (hh == 0) {
      fence_async_smem();
      __syncwarp();
      if (elect()) {
        mbar_expect_tx(bar + warp*8, 8192); (EF & 2 ? bulk_g2s_last : bulk_g2s)(sb + FN_S + warp*8192, sp + 512, 8192, bar + warp*8);
        #pragma unroll 1
        for (int i = warp; i < NS; i += 8) fill(i, i);
      }
      __syncwarp();
    }
    uint32_t pm[4];
    #pragma unroll
    for (int nt = 0; nt < 4; nt++) {
      float e[5][2];
      auto sel = [&](const uint4& v, int i) { return i == 0 ? v.x : i == 1 ? v.y : i == 2 ? v.z : v.w; };
      e[4][0] = (bflo(sel(m[0], nt)) + bflo(sel(m[1], nt))) + (bflo(sel(m[2], nt)) + bflo(sel(m[3], nt)));
      e[4][1] = (bfhi(sel(m[0], nt)) + bfhi(sel(m[1], nt))) + (bfhi(sel(m[2], nt)) + bfhi(sel(m[3], nt)));
      float mx = fmaxf(e[4][0], e[4][1]);
      #pragma unroll
      for (int kb = 0; kb <= nt; kb++) {
        const int role = nt < 2 ? 0 : 1 + (kb >> 1), i = (nt & 1)*2 + (kb & 1);
        e[kb][0] = (bflo(sel(xs[role][0], i)) + bflo(sel(xs[role][1], i))) + (bflo(sel(xs[role][2], i)) + bflo(sel(xs[role][3], i)));
        e[kb][1] = (bfhi(sel(xs[role][0], i)) + bfhi(sel(xs[role][1], i))) + (bfhi(sel(xs[role][2], i)) + bfhi(sel(xs[role][3], i)));
        if (kb == nt) { if (2*c > g) e[kb][0] = -INFINITY; if (2*c + 1 > g) e[kb][1] = -INFINITY; }
        mx = fmaxf(mx, fmaxf(e[kb][0], e[kb][1]));
      }
      mx = quad_max(mx);
      e[4][0] = ex2(e[4][0] - mx); e[4][1] = ex2(e[4][1] - mx);
      float sum = e[4][0] + e[4][1];
      #pragma unroll
      for (int kb = 0; kb <= nt; kb++) { e[kb][0] = ex2(e[kb][0] - mx); e[kb][1] = ex2(e[kb][1] - mx); sum += e[kb][0] + e[kb][1]; }
      const float inv = rcp(quad_sum(sum));
      uint32_t p[4];
      #pragma unroll
      for (int kb = 0; kb < 4; kb++) p[kb] = kb <= nt ? pack2(e[kb][0]*inv, e[kb][1]*inv) : 0u;
      pm[nt] = pack2(e[4][0]*inv, e[4][1]*inv);
      sts128(sb + FN_P + (h*5 + nt)*512 + lane*16, make_uint4(p[0], p[1], p[2], p[3]));
    }
    sts128(sb + FN_P + (h*5 + 4)*512 + lane*16, make_uint4(pm[0], pm[1], pm[2], pm[3]));
  }
  bar_sync(1, 256);
  if (tid == 0 && (s == 0 || s == 63)) TRACE(3, 24 + (s & 1)*8);
  if (warp == 7) {
    #pragma unroll 1
    for (int h = NS, sl = 0; h < 16; h++, sl = sl + 1 == NS ? 0 : sl + 1) {
      mbar_wait(bar + 160 + sl*8, (ph >> sl) & 1);
      ph ^= 1u << sl;
      if (elect()) fill(h, sl);
      __syncwarp();
    }
  } else if (NT == 4) final_mma<4>(sb, s, warp*4, ph, warp, tid);
  else final_mma<1>(sb, s, part*7 + warp, ph, warp, tid);
  bar_sync(1, 256);
  if (tid == 0 && (s == 0 || s == 63)) TRACE(3, 26 + (s & 1)*8);
  #pragma unroll 1
  for (int i = tid; i < 448*NT; i += 256) {
    const int row = NT == 4 ? i / 56 : i / 14, ch = i - row*14*NT + part*14;
    *(uint4*)(out + (size_t)(s*32 + row)*896 + 448 + ch*8) = lds128(sb + FN_O + row*OP + ch*16);
  }
  fence_async_smem();
}

__device__ __forceinline__ void final_fine(const uint32_t sb, const int s, const int part, const int nt, bf16* __restrict__ out, const int tid) {
  const int warp = __shfl_sync(0xffffffffu, tid >> 5, 0), lane = tid & 31, g = lane >> 2, c = lane & 3;
  if (lane < 28) flag_wait(F_GU + 28 + lane, (s >> 1) + 1);
  __syncwarp();
  const size_t tb = (size_t)(s*16 + warp*2)*28 + part*7;
  uint4 U[2][7][2];
  #pragma unroll
  for (int hh = 0; hh < 2; hh++)
    #pragma unroll
    for (int t = 0; t < 7; t++) { U[hh][t][0] = ldcg4(g_UF + (tb + hh*28 + t)*64 + lane); U[hh][t][1] = ldcg4(g_UF + (tb + hh*28 + t)*64 + (nt >> 1)*32 + lane); }
  { int i = 0; while (__any_sync(0xffffffffu, (int)flag_get(F_REC + warp*8 + (lane & 7)) <= s) && ++i < SPIN_MAX) __nanosleep(40); }
  if (tid == 0 && s == 63) TRACE(3, 28);
  uint32_t p[2][5];
  uint2 Wm[2][7];
  {
    uint32_t m[2][4]; uint2 xa[2][4], xb[2][4];
    #pragma unroll
    for (int hh = 0; hh < 2; hh++)
      #pragma unroll
      for (int r = 0; r < 4; r++) {
        const uint2* sp = (const uint2*)(g_SX + (size_t)((s*16 + warp*2 + hh)*4 + r)*128 + lane);
        const uint2 v = ldcg2(sp + (nt >> 1));
        m[hh][r] = (nt & 1) ? v.y : v.x;
        xa[hh][r] = ldcg2(sp + (1 + (nt >> 1))*64 + (nt & 1)); xb[hh][r] = ldcg2(sp + (1 + (nt & 2))*64 + (nt & 1));
      }
    #pragma unroll
    for (int hh = 0; hh < 2; hh++)
      #pragma unroll
      for (int t = 0; t < 7; t++) Wm[hh][t] = ldcg2(g_WD + (tb + hh*28 + t)*32 + lane);
    const int lim = 8*nt + g - 2*c;
    #pragma unroll
    for (int hh = 0; hh < 2; hh++) {
      float e[5][2], mx = -INFINITY;
      #pragma unroll
      for (int kb = 0; kb < 5; kb++) {
        uint32_t v[4];
        #pragma unroll
        for (int r = 0; r < 4; r++) v[r] = kb == 4 ? m[hh][r] : kb == 0 ? xa[hh][r].x : kb == 1 ? xa[hh][r].y : kb == 2 ? xb[hh][r].x : xb[hh][r].y;
        e[kb][0] = (bflo(v[0]) + bflo(v[1])) + (bflo(v[2]) + bflo(v[3])); e[kb][1] = (bfhi(v[0]) + bfhi(v[1])) + (bfhi(v[2]) + bfhi(v[3]));
        if (kb < 4) { if (8*kb > lim) e[kb][0] = -INFINITY; if (8*kb + 1 > lim) e[kb][1] = -INFINITY; }
        mx = fmaxf(mx, fmaxf(e[kb][0], e[kb][1]));
      }
      mx = quad_max(mx);
      float sum = 0.f;
      #pragma unroll
      for (int kb = 0; kb < 5; kb++) { e[kb][0] = ex2(e[kb][0] - mx); e[kb][1] = ex2(e[kb][1] - mx); sum += e[kb][0] + e[kb][1]; }
      const float inv = rcp(quad_sum(sum));
      #pragma unroll
      for (int kb = 0; kb < 5; kb++) p[hh][kb] = pack2(e[kb][0]*inv, e[kb][1]*inv);
    }
  }
  float acc[7][4];
  #pragma unroll
  for (int hh = 0; hh < 2; hh++) {
    #pragma unroll
    for (int t = 0; t < 7; t++) { if (hh == 0) mma16z(acc[t], U[hh][t][0].x, U[hh][t][0].y, U[hh][t][0].z, U[hh][t][0].w, p[hh][0], p[hh][1]); else mma16(acc[t], U[hh][t][0].x, U[hh][t][0].y, U[hh][t][0].z, U[hh][t][0].w, p[hh][0], p[hh][1]); }
    #pragma unroll
    for (int t = 0; t < 7; t++) mma16(acc[t], U[hh][t][1].x, U[hh][t][1].y, U[hh][t][1].z, U[hh][t][1].w, p[hh][2], p[hh][3]);
    #pragma unroll
    for (int t = 0; t < 7; t++) mma8(acc[t], Wm[hh][t].x, Wm[hh][t].y, p[hh][4]);
  }
  #pragma unroll
  for (int t = 0; t < 7; t++) sts128(sb + FN_P + (t*8 + warp)*512 + lane*16, make_uint4(__float_as_uint(acc[t][0]), __float_as_uint(acc[t][1]), __float_as_uint(acc[t][2]), __float_as_uint(acc[t][3])));
  bar_sync(1, 256);
  if (warp < 7) {
    float a[4] = {0.f, 0.f, 0.f, 0.f};
    #pragma unroll
    for (int i = 0; i < 8; i++) { const uint4 v = lds128(sb + FN_P + (warp*8 + i)*512 + lane*16); a[0] += __uint_as_float(v.x); a[1] += __uint_as_float(v.y); a[2] += __uint_as_float(v.z); a[3] += __uint_as_float(v.w); }
    const uint32_t a0 = sb + FN_O + 2*c*OP + brow_dim(warp, g)*2, a1 = a0 + (warp == 3 ? 16 : 2);
    const uint32_t lo = pack2(a[0], a[1]), hi = pack2(a[2], a[3]);
    sts16(a0, lo); sts16(a0 + OP, lo >> 16); sts16(a1, hi); sts16(a1 + OP, hi >> 16);
  }
  bar_sync(1, 256);
  if (tid < 112) { const int row = tid / 14, ch = tid - row*14; *(uint4*)(out + (size_t)(s*32 + nt*8 + row)*896 + 448 + part*112 + ch*8) = lds128(sb + FN_O + row*OP + ch*16); }
}

constexpr int PA_STAGE = 65536, PA_BAR = 229376 + 64, PA_K = 0, PA_V = 128*XP, PA_O = 256*XP;

__device__ __forceinline__ void pa1_tail(float (&acc)[3][56], const uint32_t sb, const int item, const int tid) {
  const int pt = item >> 2, hg = item & 3, par = pt & 1, i0 = (pt >> 1)*121 - 7;
  const int warp = tid >> 5, lane = tid & 31, g = lane >> 2, c = lane & 3;
  uint32_t q[14][2];
    const uint32_t da = sb + (warp*16 + (lane & 15))*XP + (lane >> 4)*16;
    #pragma unroll
    for (int b = 0; b < 14; b += 2) {
      stsm4(da + PA_K + b*16, pack2(acc[1][4*b], acc[1][4*b+1]), pack2(acc[1][4*b+2], acc[1][4*b+3]), pack2(acc[1][4*b+4], acc[1][4*b+5]), pack2(acc[1][4*b+6], acc[1][4*b+7]));
      stsm4(da + PA_V + b*16, pack2(acc[2][4*b], acc[2][4*b+1]), pack2(acc[2][4*b+2], acc[2][4*b+3]), pack2(acc[2][4*b+4], acc[2][4*b+5]), pack2(acc[2][4*b+6], acc[2][4*b+7]));
    }
    #pragma unroll
    for (int b = 0; b < 14; b++) { q[b][0] = pack2(acc[0][4*b], acc[0][4*b+1]); q[b][1] = pack2(acc[0][4*b+2], acc[0][4*b+3]); }
  bar_sync(1, 256);
  if (tid == 0 && item == 40) TRACE(1, 42);
  const float sc = 0.18898223650461362f*1.4426950408889634f;
  const int row = i0 + warp*16 + g;
  const bool ok0 = warp*16 + g >= 7;
  const uint32_t oa = sb + PA_O + (warp*16 + (lane & 15))*XP;
  const bool d0 = 2*c <= g, d1 = 2*c + 1 <= g;
  const bool v0 = d0 ? row - g + 2*c >= 0 : row - g + 2*c - 8 >= 0, v1 = d1 ? row - g + 2*c + 1 >= 0 : row - g + 2*c - 7 >= 0;
  const bool v2 = d0 || row - g + 2*c >= 0, v3 = d1 || row - g + 2*c + 1 >= 0;
  uint32_t keep[2];
  #pragma unroll
  for (int hd = 0; hd < 4; hd++) {
    const int b0 = (hd >> 1)*7 + (hd & 1)*3;
    uint32_t qa[4][2];
    #pragma unroll
    for (int i = 0; i < 4; i++) {
      const bool half = i == ((hd & 1) ? 0 : 3), on = (hd & 1) ? c >= 2 : c < 2;
      qa[i][0] = half && !on ? 0u : q[b0 + i][0]; qa[i][1] = half && !on ? 0u : q[b0 + i][1];
    }
    float S[3][4];
    uint32_t vb[3][4];
    #pragma unroll
    for (int nt = 0; nt < 3; nt++) {
      const int kr = warp*16 - 8 + nt*8;
      const uint32_t ra = sb + ((kr < 0 ? 0 : kr) + (lane & 7))*XP + (b0 + (lane >> 3))*16;
      uint32_t kb[4];
      ldsm4(kb, ra + PA_K); ldsm4t(vb[nt], ra + PA_V);
      mma16z(S[nt], qa[0][0], qa[0][1], qa[1][0], qa[1][1], kb[0], kb[1]);
      mma16(S[nt], qa[2][0], qa[2][1], qa[3][0], qa[3][1], kb[2], kb[3]);
    }
    float e0 = v0 ? (d0 ? S[1][0] : S[0][0])*sc : -INFINITY, e1 = v1 ? (d1 ? S[1][1] : S[0][1])*sc : -INFINITY;
    float e2 = v2 ? (d0 ? S[2][2] : S[1][2])*sc : -INFINITY, e3 = v3 ? (d1 ? S[2][3] : S[1][3])*sc : -INFINITY;
    const float ma = fmaxf(quad_max(fmaxf(e0, e1)), -3.0e38f), mb = quad_max(fmaxf(e2, e3));
    e0 = ex2(e0 - ma); e1 = ex2(e1 - ma); e2 = ex2(e2 - mb); e3 = ex2(e3 - mb);
    const float ia = rcp(quad_sum(e0 + e1)), ib = rcp(quad_sum(e2 + e3));
    const uint32_t pa = ok0 ? pack2(e0*ia, e1*ia) : 0u, pb = pack2(e2*ib, e3*ib);
    const uint32_t dm = (d0 ? 0xffffu : 0u) | (d1 ? 0xffff0000u : 0u);
    #pragma unroll
    for (int i = 0; i < 4; i++) {
      float o[4];
      mma16z(o, pa & ~dm, 0u, pa & dm, pb & ~dm, vb[0][i], vb[1][i]);
      mma8(o, 0u, pb & dm, vb[2][i]);
      uint32_t r0 = pack2(o[0], o[1]), r1 = pack2(o[2], o[3]);
      if (!(hd & 1) && i == 3) { keep[0] = r0; keep[1] = r1; continue; }
      if ((hd & 1) && i == 0 && c < 2) { r0 = keep[0]; r1 = keep[1]; }
      stsm2(oa + (b0 + i)*16, r0, r1);
    }
  }
  __syncwarp();
  #pragma unroll
  for (int i = 0; i < 7; i++) {
    const int j = i*32 + lane, rr = warp*16 + j / 14, ch = j % 14;
    if (rr >= 7 && i0 + rr < 1024) *(uint4*)(g_OA + (size_t)(2*(i0 + rr) + par)*448 + hg*112 + ch*8) = lds128(sb + PA_O + rr*XP + ch*16);
  }
  fence_async();
  fence_async_smem();
  bar_sync(1, 256);
  if (tid == 0 && item == 40) TRACE(1, 43);
  if (tid == 255) flag_add(F_A1 + pt);
  if (tid == 0 && item == 40) TRACE(1, 44);
}

__device__ __forceinline__ void pa2_tail(float (&acc)[3][56], const uint32_t sb, const int item, bf16* __restrict__ out, const int tid) {
  const int tile = item >> 1, nh = item & 1, warp = tid >> 5, lane = tid & 31;
  const uint32_t da = sb + (warp*16 + (lane & 15))*464 + (lane >> 4)*16;
  #pragma unroll
  for (int p = 0; p < 2; p++)
    #pragma unroll
    for (int b = 0; b < 14; b += 2)
      stsm4(da + p*224 + b*16, pack2(acc[p][4*b], acc[p][4*b+1]), pack2(acc[p][4*b+2], acc[p][4*b+3]), pack2(acc[p][4*b+4], acc[p][4*b+5]), pack2(acc[p][4*b+6], acc[p][4*b+7]));
  __syncwarp();
  #pragma unroll
  for (int i = 0; i < 14; i++) {
    const int j = i*32 + lane, rr = warp*16 + j / 28, ch = j % 28;
    *(uint4*)(out + (size_t)(tile*128 + rr)*896 + nh*224 + ch*8) = lds128(sb + rr*464 + ch*16);
  }
  fence_async_smem();
  bar_sync(1, 256);
  if (tid == 0 && item == 10) TRACE(1, 47);
}

__device__ __forceinline__ void pa_item(const Maps& mp, const uint32_t sb, const int item, bf16* __restrict__ out, uint32_t& ph, const int tid) {
  const bool first = item < 72;
  const int it2 = item - 72, warp = __shfl_sync(0xffffffffu, tid >> 5, 0);
  if (!first) {
    if (tid < 4) flag_wait(F_A1 + (((it2 >> 1)*64 + (tid >> 1)*63) / 121)*2 + (tid & 1), 4);
    bar_sync(1, 256);
  }
  if (tid == 0 && (item == 40 || item == 82)) TRACE(1, first ? 40 : 45);
  const CUtensorMap* ma = first ? &mp.ax : &mp.oa; const CUtensorMap* mb = first ? &mp.aw : &mp.ao;
  const int a0 = first ? ((item >> 2) & 1)*448 : 0, a1 = first ? (item >> 3)*121 - 7 : (it2 >> 1)*128;
  const int col0 = first ? (item & 3)*112 : (it2 & 1)*224, cstep = first ? 448 : 112, np = first ? 3 : 2;
  const uint32_t bar = sb + PA_BAR;
  float acc[3][56];
  #pragma unroll
  for (int i = 0; i < 168; i++) acc[i / 56][i % 56] = 0.f;
  #pragma unroll 1
  for (int kc = -1, sg = 2; kc < 7; kc++, sg = sg == 2 ? 0 : sg + 1) {
    if (kc >= 0) {
      const uint32_t al = wg_lo(sb + sg*PA_STAGE + (warp >> 2)*8192, 16), bl = wg_lo(sb + sg*PA_STAGE + 16384, 8192);
      mbar_wait(bar + sg*8, (ph >> sg) & 1);
      ph ^= 1 << sg;
      if (first) { wg_fence(); static_for<0, 12>([&](auto j) { wg_ss112<0, DH_SW, (j.value / 3)*32, 1, DH_SW, (j.value % 3)*16384 + (j.value / 3)*2048>(acc[j.value % 3], al, bl, 1); }); wg_commit(); }
      else { wg_fence(); static_for<0, 8>([&](auto j) { wg_ss112<0, DH_SW, (j.value >> 1)*32, 1, DH_SW, (j.value & 1)*16384 + (j.value >> 1)*2048>(acc[j.value & 1], al, bl, 1); }); wg_commit(); }
      wg_wait<1>();
    }
    if (kc != 0 && kc < 5) {
      if (kc > 0) bar_sync(1, 256);
      if (warp < (kc < 0 ? 3 : 1) && elect()) {
        const int k = kc < 0 ? warp : kc + 2, s2 = kc < 0 ? warp : sg == 0 ? 2 : sg - 1;
        const uint32_t st = sb + s2*PA_STAGE, b = bar + s2*8;
        mbar_expect_tx(b, 16384 + np*16384);
        tma2d(st, ma, a0 + k*64, a1, b);
        #pragma unroll 1
        for (int p = 0; p < 2*np; p++) tma2d(st + 16384 + p*8192, mb, col0 + (p >> 1)*cstep + (p & 1)*64, k*64, b);
      }
      __syncwarp();
    }
  }
  wg_wait<0>();
  #pragma unroll
  for (int p = 0; p < 3; p++) wg_pin(acc[p]);
  if (tid == 0 && (item == 40 || item == 82)) TRACE(1, first ? 41 : 46);
  bar_sync(1, 256);
  if (first) pa1_tail(acc, sb, item, tid); else pa2_tail(acc, sb, it2, out, tid);
}
__device__ __forceinline__ void pa_init(const uint32_t sb) { for (int i = 0; i < 3; i++) mbar_init(sb + PA_BAR + i*8, 1); }

#define FETCH_DELAY 460
#define OVERLAP 1
#define REC_LAG 3000
#define STAGGER 80
#define DAMP 100
#define NUDGE 40
#define LEAD 24
#define A_GAP -1
#define NQUART 60
#define NWHOLE 57

__global__ void __cluster_dims__(4,1,1) __launch_bounds__(256, 1) rec_kernel(const __grid_constant__ Maps mp, int delay, int ring) {
  extern __shared__ __align__(1024) uint8_t smem[];
  const uint32_t sb = __shfl_sync(0xffffffffu, smem_u32(smem), 0);
  const int tid = threadIdx.x, lane = tid & 31;
  const int warp = __shfl_sync(0xffffffffu, tid >> 5, 0), w = warp & 3;
  const int bid = __shfl_sync(0xffffffffu, blockIdx.x, 0), h = bid >> 2, r = bid & 3;
  asm volatile("griddepcontrol.launch_dependents;");
  if (tid == 0) TRACE(2, 0);
  rec_init(sb, tid);
  if (tid == 0) asm volatile("fence.mbarrier_init.release.cluster;" ::: "memory");
  __syncthreads();
  cluster_sync();
  { const uint32_t t0 = clk(); while (clk() - t0 < REC_LAG) {} }
  switch (warp >> 1) {
    case 0: rec_warp<1>(sb, lane, w, h, r, &mp.x120, delay, ring); break;
    case 1: rec_warp<0>(sb, lane, w, h, r, &mp.x120, delay, ring); break;
    case 2: rec_warp<2>(sb, lane, w, h, r, &mp.x120, delay, ring); break;
    default: rec_warp<3>(sb, lane, w, h, r, &mp.x120, delay, ring); break;
  }
  cluster_sync();
}

__global__ void __launch_bounds__(384, 1) bulk_kernel(const __grid_constant__ Maps mp, bf16* __restrict__ out, int mode, int lead) {
  extern __shared__ __align__(1024) uint8_t smem[];
  const uint32_t sb = __shfl_sync(0xffffffffu, smem_u32(smem), 0);
  const int tid = threadIdx.x, lane = tid & 31;
  const int warp = __shfl_sync(0xffffffffu, tid >> 5, 0);
  if (tid == 0) TRACE((mode & 1) ? 1 : 3, 0);
  if (tid == 0) { gemm_init(sb); pa_init(sb); final_init(sb); asm volatile("fence.mbarrier_init.release.cluster;" ::: "memory"); }
  __syncthreads();
  if (mode & 1) {
    cluster_sync();
    if (warp == 8) gemm_aux(mp, sb, blockIdx.x, lane, lead, -2, 0);
    asm volatile("griddepcontrol.wait;" ::: "memory");
    asm volatile("griddepcontrol.launch_dependents;");
    if (tid == 0) TRACE(1, 35);
  }
  if (warp < 8) {
    asm volatile("setmaxnreg.inc.sync.aligned.u32 232;");
    if (mode & 1) gemm_wg(sb, blockIdx.x, warp, lane);
    uint32_t ph = 0, fph = 0;
    int na = 0;
    #pragma unroll 1
    while (mode & 6) {
      if (tid == 0) {
        bool a = mode & 2;
        if (a && (mode & 5) == 4) { const int nx = flag_get(F_Q2), pr = flag_get(F_REC); a = nx >= NWHOLE || nx + (pr ? 0 : 2 - 4*na) > pr + A_GAP; }
        sts32(sb + PA_BAR + 24, a ? atomicAdd(g_flag + F_Q1*32, 1) : 1024 + atomicAdd(g_flag + F_Q2*32, 1));
      }
      bar_sync(1, 256);
      const int item = lds32(sb + PA_BAR + 24);
      bar_sync(1, 256);
      if (item < 1024) {
        if (item < 104) { pa_item(mp, sb, item, out, ph, tid); na++; if (tid == 0) TRACE((mode & 1) ? 1 : 3, (mode & 1) ? 34 : 1); } else mode &= ~2;
      } else {
        const int i = item - 1024, j = i - NWHOLE, k = j - 4*(NQUART - NWHOLE);
        if (k < 0) { final_item(sb, j < 0 ? i : NWHOLE + (j >> 2), j < 0 ? 4 : 1, j < 0 ? 0 : j & 3, out, fph, tid); if (tid == 0) TRACE(0, 8 + (j < 0 ? i : NWHOLE + (j >> 2))); }
        else if (k < 16*(NSEG - NQUART)) { final_fine(sb, NQUART + (k >> 4), k & 3, (k >> 2) & 3, out, tid); if (tid == 0) TRACE(0, 8 + NQUART + (k >> 4)); }
        else mode &= ~4;
      }
    }
  } else {
    asm volatile("setmaxnreg.dec.sync.aligned.u32 40;");
    if (warp == 8 && (mode & 1)) gemm_aux(mp, sb, blockIdx.x, lane, lead, 0, 32);
  }
}

typedef CUresult (*EncFn)(CUtensorMap*, CUtensorMapDataType, cuuint32_t, void*, const cuuint64_t*, const cuuint64_t*, const cuuint32_t*, const cuuint32_t*, CUtensorMapInterleave, CUtensorMapSwizzle, CUtensorMapL2promotion, CUtensorMapFloatOOBfill);
static void make_map(EncFn enc, CUtensorMap* m, const void* ptr, uint64_t cols, uint64_t rows, uint32_t bc, uint32_t br, bool swz) {
  cuuint64_t dims[2] = {cols, rows}; cuuint64_t str[1] = {cols*2}; cuuint32_t box[2] = {bc, br}; cuuint32_t es[2] = {1, 1};
  enc(m, CU_TENSOR_MAP_DATA_TYPE_BFLOAT16, 2, (void*)ptr, dims, str, box, es, CU_TENSOR_MAP_INTERLEAVE_NONE, swz ? CU_TENSOR_MAP_SWIZZLE_128B : CU_TENSOR_MAP_SWIZZLE_NONE,
      CU_TENSOR_MAP_L2_PROMOTION_L2_128B, CU_TENSOR_MAP_FLOAT_OOB_FILL_NONE);
}
static int h_delay = FETCH_DELAY | ((FETCH_DELAY - STAGGER) << 16), h_lead = LEAD, h_damp = DAMP, h_nudge = NUDGE;

extern "C" void kernel_launch(void* const* d_in, const int* in_sizes, int n_in, void* d_out, int out_size) {
  bf16* out = (bf16*)d_out;
  void* fn = nullptr; cudaDriverEntryPointQueryResult qr;
  cudaGetDriverEntryPoint("cuTensorMapEncodeTiled", &fn, cudaEnableDefault, &qr);
  EncFn enc = (EncFn)fn;
  void* oa = nullptr; cudaGetSymbolAddress(&oa, g_OA);
  Maps mp;
  make_map(enc, &mp.wq, d_in[5], 4096, 448, 64, 64, true);
  make_map(enc, &mp.wk, d_in[6], 4096, 448, 64, 224, true);
  make_map(enc, &mp.wv, d_in[7], 4096, 448, 64, 224, true);
  make_map(enc, &mp.wo, d_in[8], 448, 4096, 64, 64, true);
  make_map(enc, &mp.x120, d_in[3], 448, 2048, 120, 32, false);
  make_map(enc, &mp.x64, d_in[3], 448, 2048, 64, 64, true);
  make_map(enc, &mp.ax, d_in[0], 896, 1024, 64, 128, true);
  make_map(enc, &mp.aw, d_in[1], 1344, 448, 64, 64, true);
  make_map(enc, &mp.ao, d_in[2], 448, 448, 64, 64, true);
  make_map(enc, &mp.oa, oa, 448, 2048, 64, 128, true);
  cudaFuncSetAttribute(prep_kernel, cudaFuncAttributeMaxDynamicSharedMemorySize, PR_SMEM);
  cudaFuncSetAttribute(rec_kernel, cudaFuncAttributeMaxDynamicSharedMemorySize, REC_SMEM);
  cudaFuncSetAttribute(bulk_kernel, cudaFuncAttributeMaxDynamicSharedMemorySize, GM_SMEM);
  cudaStream_t st = cudaStreamPerThread;
  int sms = 0, ncl = 0;
  cudaDeviceGetAttribute(&sms, cudaDevAttrMultiProcessorCount, 0);
  {
    cudaLaunchConfig_t cfg = {}; cfg.gridDim = dim3(120); cfg.blockDim = dim3(256); cfg.dynamicSmemBytes = REC_SMEM;
    cudaLaunchAttribute at; at.id = cudaLaunchAttributeClusterDimension; at.val.clusterDim.x = 4; at.val.clusterDim.y = 1; at.val.clusterDim.z = 1;
    cfg.attrs = &at; cfg.numAttrs = 1;
    cudaOccupancyMaxActiveClusters(&ncl, rec_kernel, &cfg);
  }
  prep_kernel<<<132, 256, PR_SMEM, st>>>(mp, (const bf16*)d_in[4]);
  const bool ov = OVERLAP && ncl >= 30 && sms >= 124;
  cudaLaunchAttribute at[2], &cl = at[0], &pdl = at[1];
  cl.id = cudaLaunchAttributeClusterDimension; cl.val.clusterDim.x = 4; cl.val.clusterDim.y = 1; cl.val.clusterDim.z = 1;
  pdl.id = cudaLaunchAttributeProgrammaticStreamSerialization; pdl.val.programmaticStreamSerializationAllowed = 1;
  cudaLaunchConfig_t cfg = {}; cfg.stream = st;
  cfg.gridDim = dim3(56); cfg.blockDim = dim3(384); cfg.dynamicSmemBytes = GM_SMEM; cfg.attrs = at; cfg.numAttrs = 2;
  cudaLaunchKernelEx(&cfg, bulk_kernel, mp, out, ov ? 7 : 3, ov ? h_lead : 64);
  cfg.gridDim = dim3(64); cfg.blockDim = dim3(256); cfg.dynamicSmemBytes = REC_SMEM; cfg.attrs = &pdl; cfg.numAttrs = ov;
  cudaLaunchKernelEx(&cfg, rec_kernel, mp, h_delay, 63 | (h_nudge << 8) | (h_damp << 16));
  cfg.gridDim = dim3(ov ? sms - 120 : sms); cfg.blockDim = dim3(384); cfg.dynamicSmemBytes = GM_SMEM;
  cudaLaunchKernelEx(&cfg, bulk_kernel, mp, out, ov ? 6 : 4, 0);
}
```
